```python
import torch

def _softmax(x, axis=-1):
    return torch.softmax(x, dim=axis)
def _gelu(x):
    return torch.nn.functional.gelu(x, approximate="tanh")
def _silu(x):
    return torch.nn.functional.silu(x)
def _sigmoid(x):
    return torch.sigmoid(x)
def _layernorm(x, axis=-1, eps=1e-5):
    m = x.mean(dim=axis, keepdim=True)
    v = x.var(dim=axis, keepdim=True, unbiased=False)
    return (x - m) / torch.sqrt(v + eps)
def _scatter_add(tgt, idx, src, axis=0):
    return tgt.clone().index_add_(axis, idx, src)
def _segment_sum(src, seg, n):
    out = torch.zeros((n,) + src.shape[1:], dtype=src.dtype)
    return out.index_add_(0, seg, src)
def _pad(x, pw):
    flat = tuple(v for pair in reversed(pw) for v in pair)
    return torch.nn.functional.pad(x, flat)

kernel_name = 'parallel_sum__sliding_block_cached__dense_activation_mish__decode'

def setup_inputs():

    _w = (lambda a: (lambda t: t.to(torch.bfloat16) if t.is_floating_point() else t)(torch.as_tensor(a)))
    def _A_setup():
        B, Sq, D = 4, 1, 576
        Hq, Hkv, Sk, Dh = 32, 16, 4096, 128
        assert Hq % Hkv == 0, (Hq, Hkv)
        return {
            "x": _w((lambda *s: torch.randn(*s, dtype=torch.bfloat16) * 0.05)(B, Sq, D)),
            "k_cache": _w((lambda *s: torch.randn(*s, dtype=torch.bfloat16) * 1.6)(B, Hkv, Sk, Dh)),
            "v_cache": _w((lambda *s: torch.randn(*s, dtype=torch.bfloat16) * 0.4)(B, Hkv, Sk, Dh)),
            "wq": _w((lambda *s: torch.randn(*s, dtype=torch.bfloat16) * 1.6)(D, Hq * Dh) * (D ** -0.5)),
            "wo": _w((lambda *s: torch.randn(*s, dtype=torch.bfloat16) * 0.4)(Hq * Dh, D) * ((Hq * Dh) ** -0.5)),
        }
    _A_in = _A_setup()

    def _B_setup():
        B, S, D, F = 4, 1, 576, 4608
        return {
            "x": _w((lambda *s: torch.randn(*s, dtype=torch.bfloat16) * 0.05)(B, S, D)),
            "w1": _w((lambda *s: torch.randn(*s, dtype=torch.bfloat16) * 0.4)(D, F) * (D ** -0.5)),
            "b1": _w((lambda *s: torch.randn(*s, dtype=torch.bfloat16) * 0.2)(F)),
            "w2": _w((lambda *s: torch.randn(*s, dtype=torch.bfloat16) * 0.2)(F, D) * (F ** -0.5)),
        }
    _B_in = _B_setup()

    return {
        "A_x": _A_in["x"],
        "A_k_cache": _A_in["k_cache"],
        "A_v_cache": _A_in["v_cache"],
        "A_wq": _A_in["wq"],
        "A_wo": _A_in["wo"],
        "B_x": _B_in["x"],
        "B_w1": _B_in["w1"],
        "B_b1": _B_in["b1"],
        "B_w2": _B_in["w2"],
    }

def reference(A_x, A_k_cache, A_v_cache, A_wq, A_wo, B_x, B_w1, B_b1, B_w2):
    def _A_ref(x, k_cache, v_cache, wq, wo):
        B, Sq, D = x.shape
        Hq, Dh = 32, 128
        Hkv, Sk = k_cache.shape[1], k_cache.shape[2]
        W = min(4096, max(256, Sk // 4))
        rep = Hq // Hkv
        q = (lambda x, *d: x.permute(*d))((x @ wq).reshape(B, Sq, Hq, Dh), 0, 2, 1, 3)
        k = (lambda x, n, axis: torch.repeat_interleave(x, n, dim=axis))(k_cache[:, :, Sk - W:, :], rep, axis=1)
        v = (lambda x, n, axis: torch.repeat_interleave(x, n, dim=axis))(v_cache[:, :, Sk - W:, :], rep, axis=1)
        scores = torch.einsum("bhqd,bhkd->bhqk", q, k) * (Dh ** -0.5)
        p = _softmax(scores, axis=-1)
        o = torch.einsum("bhqk,bhkd->bhqd", p, v)
        return (lambda x, *d: x.permute(*d))(o, 0, 2, 1, 3).reshape(B, Sq, Hq * Dh) @ wo

    def _B_ref(x, w1, b1, w2):
        h = torch.einsum("bsd,df->bsf", x, w1) + b1
        sp = torch.log1p(torch.exp(-torch.abs(h))) + torch.where(h > 0, h, torch.zeros_like(h))
        act = h * torch.tanh(sp)
        return torch.einsum("bsf,fd->bsd", act, w2)

    x = A_x
    xn = _layernorm(x, axis=-1)
    return x + _A_ref(xn, A_k_cache, A_v_cache, A_wq, A_wo) + _B_ref(xn, B_w1, B_b1, B_w2)
```

```cpp
#include <cuda_runtime.h>
#include <cuda.h>
#include <cuda_bf16.h>
#include <stdint.h>

#define DEVINL __device__ __forceinline__

namespace {

constexpr int NB = 4;
constexpr int DM = 576;
constexpr int HQ = 32, HKV = 16, SK = 4096, DH = 128, WIN = 1024;
constexpr int FF = 4608;
constexpr int QD = HQ * DH;

constexpr int NATT = 128;
constexpr int NCTA = 132;
constexpr int NRED = 72;
constexpr int RED0 = NCTA - NRED;
constexpr int NTHREADS = 320;

constexpr int SLOT_BYTES = 16384;
constexpr int NSLOT = 6;
constexpr int REG_BYTES = 36864;
constexpr int HALF_BYTES = REG_BYTES / 2;
constexpr int OFF_WA = NSLOT * SLOT_BYTES;
constexpr int OFF_WB = OFF_WA + REG_BYTES;
constexpr int OFF_WC = OFF_WB + REG_BYTES;
constexpr int OFF_MISC = OFF_WC + REG_BYTES;
constexpr int XPITCH = 584;
constexpr int OFF_XN = OFF_MISC;
constexpr int OFF_RED = OFF_XN + NB * XPITCH * 2;
constexpr int OFF_Q = OFF_RED + 2048;
constexpr int OFF_ACT = OFF_Q + 512;
constexpr int OFF_O = OFF_ACT + 1280;
constexpr int OFF_ML = OFF_O + 320;
constexpr int OFF_BAR = OFF_ML + 128;
constexpr int OFF_OP = OFF_BAR + 336;
constexpr int SMEM_BYTES = OFF_OP + 8192;
static_assert(SMEM_BYTES <= 232448, "smem");
static_assert(OFF_RED % 16 == 0 && OFF_Q % 16 == 0 && OFF_OP % 16 == 0 && OFF_BAR % 8 == 0, "align");
static_assert(5 * REG_BYTES <= OFF_MISC, "ffn cta regions");
static_assert(OFF_WA % 1024 == 0 && HALF_BYTES % 1024 == 0, "swizzle atom alignment");

constexpr int APITCH = 40;

constexpr int BAR_FULL = 0;
constexpr int BAR_EMPTY = 24;
constexpr int BAR_WQFREE = 34, BAR_Q = 35, BAR_O = 36, BAR_GO = 37, BAR_GO1 = 38;
constexpr int NBAR = 39;

#define PACE_A 3
#define PACE 4
#define PACE_END 2
#define PACE_FIN 3
#define NFILL 4
#define TRIG1 0

constexpr unsigned SPIN_LIMIT = 1u << 20;

__device__ uint32_t g_qbox[NATT * 128];
__device__ uint32_t g_obox[NATT * 8 * 64];
__device__ uint32_t g_part[NRED * NCTA * 32];
__device__ unsigned long long g_done;

__device__ __nv_bfloat16 g_fb_q[NB * QD];
__device__ __nv_bfloat16 g_fb_act[NB * FF];
__device__ __nv_bfloat16 g_fb_o[NB * QD];

#define TL(i) do {} while (0)

DEVINL uint32_t smem_u32(const void* p) { return (uint32_t)__cvta_generic_to_shared(p); }

DEVINL void mbar_init(uint32_t bar, uint32_t cnt) {
    asm volatile("mbarrier.init.shared::cta.b64 [%0], %1;" ::"r"(bar), "r"(cnt) : "memory");
}
DEVINL void mbar_expect_tx(uint32_t bar, uint32_t bytes) {
    asm volatile("mbarrier.arrive.expect_tx.shared::cta.b64 _, [%0], %1;" ::"r"(bar), "r"(bytes) : "memory");
}
DEVINL void mbar_arrive(uint32_t bar) {
    asm volatile("mbarrier.arrive.shared::cta.b64 _, [%0];" ::"r"(bar) : "memory");
}
DEVINL void mbar_wait(uint32_t bar, uint32_t parity) {
    uint32_t ok = 0;
    for (unsigned it = 0; it < SPIN_LIMIT; ++it) {
        asm volatile(
            "{\n\t.reg .pred p;\n\t"
            "mbarrier.try_wait.parity.shared::cta.b64 p, [%1], %2;\n\t"
            "selp.u32 %0, 1, 0, p;\n\t}"
            : "=r"(ok) : "r"(bar), "r"(parity) : "memory");
        if (ok) break;
    }
}
DEVINL bool mbar_test(uint32_t bar, uint32_t parity) {
    uint32_t ok;
    asm volatile(
        "{\n\t.reg .pred p;\n\t"
        "mbarrier.test_wait.parity.shared::cta.b64 p, [%1], %2;\n\t"
        "selp.u32 %0, 1, 0, p;\n\t}"
        : "=r"(ok) : "r"(bar), "r"(parity) : "memory");
    return ok != 0;
}
DEVINL void tma_2d(uint32_t dst, const CUtensorMap* map, int c0, int c1, uint32_t bar) {
    asm volatile(
        "cp.async.bulk.tensor.2d.shared::cluster.global.mbarrier::complete_tx::bytes [%0], [%1, {%2, %3}], [%4];"
        ::"r"(dst), "l"(map), "r"(c0), "r"(c1), "r"(bar) : "memory");
}
DEVINL void prefetch_tmap(const CUtensorMap* map) {
    asm volatile("prefetch.tensormap [%0];" ::"l"(map) : "memory");
}
DEVINL bool elect_one() {
    uint32_t p;
    asm volatile("{\n\t.reg .pred P;\n\telect.sync _|P, 0xffffffff;\n\tselp.u32 %0, 1, 0, P;\n\t}" : "=r"(p));
    return p != 0;
}
DEVINL void cbar() { asm volatile("bar.sync 1, 256;" ::: "memory"); }

DEVINL void ldsm4t(uint32_t addr, uint32_t& r0, uint32_t& r1, uint32_t& r2, uint32_t& r3) {
    asm volatile("ldmatrix.sync.aligned.m8n8.x4.trans.shared.b16 {%0,%1,%2,%3}, [%4];"
                 : "=r"(r0), "=r"(r1), "=r"(r2), "=r"(r3) : "r"(addr) : "memory");
}
DEVINL uint4 lds128(uint32_t addr) {
    uint4 v;
    asm volatile("ld.shared.v4.u32 {%0,%1,%2,%3}, [%4];" : "=r"(v.x), "=r"(v.y), "=r"(v.z), "=r"(v.w) : "r"(addr) : "memory");
    return v;
}
DEVINL uint32_t lds32(uint32_t addr) {
    uint32_t v;
    asm volatile("ld.shared.u32 %0, [%1];" : "=r"(v) : "r"(addr) : "memory");
    return v;
}
DEVINL void mma16816(float* c, uint32_t a0, uint32_t a1, uint32_t a2, uint32_t a3, uint32_t b0, uint32_t b1) {
    asm volatile(
        "mma.sync.aligned.m16n8k16.row.col.f32.bf16.bf16.f32 {%0,%1,%2,%3}, {%4,%5,%6,%7}, {%8,%9}, {%0,%1,%2,%3};"
        : "+f"(c[0]), "+f"(c[1]), "+f"(c[2]), "+f"(c[3])
        : "r"(a0), "r"(a1), "r"(a2), "r"(a3), "r"(b0), "r"(b1));
}
DEVINL uint32_t pack_bf16(float lo, float hi) {
    uint32_t r;
    asm("cvt.rn.bf16x2.f32 %0, %1, %2;" : "=r"(r) : "f"(hi), "f"(lo));
    return r;
}
DEVINL float bf16r(float x) { return __bfloat162float(__float2bfloat16_rn(x)); }
DEVINL float bf_lo(uint32_t w) { return __uint_as_float(w << 16); }
DEVINL float bf_hi(uint32_t w) { return __uint_as_float(w & 0xffff0000u); }

DEVINL uint32_t enc(uint32_t w) { return w ? w : 0x80000000u; }
DEVINL uint32_t encf(float f) { return enc(__float_as_uint(f)); }
DEVINL void st_rlx(uint32_t* p, uint32_t v) {
    asm volatile("st.relaxed.gpu.global.u32 [%0], %1;" ::"l"(p), "r"(v) : "memory");
}
DEVINL void st_rlx4(uint32_t* p, uint4 v) {
    asm volatile("st.relaxed.gpu.global.v4.u32 [%0], {%1,%2,%3,%4};" ::"l"(p), "r"(v.x), "r"(v.y), "r"(v.z), "r"(v.w) : "memory");
}
DEVINL uint32_t ld_rlx(const uint32_t* p) {
    uint32_t v;
    asm volatile("ld.relaxed.gpu.global.u32 %0, [%1];" : "=r"(v) : "l"(p) : "memory");
    return v;
}
DEVINL uint4 ld_rlx4(const uint32_t* p) {
    uint4 v;
    asm volatile("ld.relaxed.gpu.global.v4.u32 {%0,%1,%2,%3}, [%4];" : "=r"(v.x), "=r"(v.y), "=r"(v.z), "=r"(v.w) : "l"(p) : "memory");
    return v;
}
DEVINL unsigned long long ld_rlx64(const unsigned long long* p) {
    unsigned long long v;
    asm volatile("ld.relaxed.gpu.global.u64 %0, [%1];" : "=l"(v) : "l"(p) : "memory");
    return v;
}
DEVINL void red_add64(unsigned long long* p, unsigned long long v) {
    asm volatile("red.relaxed.gpu.global.add.u64 [%0], %1;" ::"l"(p), "l"(v) : "memory");
}
DEVINL bool all_set(uint4 v) { return v.x && v.y && v.z && v.w; }

DEVINL float mish(float h) {
    float sp = log1pf(expf(-fabsf(h))) + fmaxf(h, 0.f);
    return h * tanhf(sp);
}

DEVINL void col_gemv(uint32_t wbase, uint32_t xn_s, float* red, int warp, int lane) {
    const int mt = warp & 1, kg = warp >> 1;
    const int g = lane >> 2, t = lane & 3;
    const int j = lane >> 3, r = lane & 7;
    const int chunk = 2 * mt + (j & 1);
    const uint32_t aaddr = wbase + (kg * 144 + (j >> 1) * 8 + r) * 64 + ((chunk ^ ((r >> 1) & 3)) << 4);
    const uint32_t baddr = xn_s + ((g & 3) * XPITCH + kg * 144 + 2 * t) * 2;
    float acc[3][4] = {};
#pragma unroll
    for (int ks = 0; ks < 9; ++ks) {
        uint32_t a0, a1, a2, a3;
        ldsm4t(aaddr + ks * 1024, a0, a1, a2, a3);
        uint32_t b0 = lds32(baddr + ks * 32), b1 = lds32(baddr + ks * 32 + 16);
        if (g >= 4) { b0 = 0; b1 = 0; }
        mma16816(acc[ks % 3], a0, a1, a2, a3, b0, b1);
    }
    if (t < 2) {
        float2 v0 = make_float2(acc[0][0] + acc[1][0] + acc[2][0], acc[0][1] + acc[1][1] + acc[2][1]);
        float2 v1 = make_float2(acc[0][2] + acc[1][2] + acc[2][2], acc[0][3] + acc[1][3] + acc[2][3]);
        *reinterpret_cast<float2*>(red + (kg * 32 + 16 * mt + g) * 4 + 2 * t) = v0;
        *reinterpret_cast<float2*>(red + (kg * 32 + 16 * mt + g + 8) * 4 + 2 * t) = v1;
    }
}

DEVINL void row_gemv16(uint32_t wbase, uint32_t v_s, float (&acc)[5][4], int warp, int lane) {
    const int g = lane >> 2, t = lane & 3;
    const int j = lane >> 3, r = lane & 7;
    const int nb = 2 * warp + (j & 1);
    const int line0 = ((j >> 1) * 8 + r) * 9 + (nb >> 3);
    const uint32_t baddr = v_s + ((g & 3) * APITCH + 2 * t) * 2;
    uint32_t b0 = lds32(baddr), b1 = lds32(baddr + 16);
    if (g >= 4) { b0 = 0; b1 = 0; }
#pragma unroll
    for (int i = 0; i < 5; ++i) {
        if (i < 4 || warp < 4) {
            const int line = line0 + 2 * i;
            uint32_t a0, a1, a2, a3;
            ldsm4t(wbase + line * 128 + (((nb ^ line) & 7) << 4), a0, a1, a2, a3);
            mma16816(acc[i], a0, a1, a2, a3, b0, b1);
        }
    }
}

struct Maps { CUtensorMap wq, k, v, w1, w2, wo; };

__global__ void __launch_bounds__(NTHREADS, 1)
fused_kernel(const __grid_constant__ Maps mp, const __nv_bfloat16* __restrict__ x,
             const __nv_bfloat16* __restrict__ b1, __nv_bfloat16* __restrict__ out) {
    extern __shared__ __align__(1024) unsigned char smem[];
    const uint32_t sb = smem_u32(smem);
    const int tid = threadIdx.x, warp = tid >> 5, lane = tid & 31;
    const int cta = blockIdx.x;
    const bool is_att = cta < NATT;
    const int kvh = cta >> 3, rk = cta & 7;
    const uint32_t bars = sb + OFF_BAR;
    auto BAR = [&](int i) { return bars + 8u * i; };
    const int funit = is_att ? cta : NATT + (cta - NATT) * 4;
    const int kvline = (((rk >> 1) * HKV + kvh) * SK + (SK - WIN) + (rk & 1) * (WIN / 2)) * 2;

    if (tid == 256) {
        prefetch_tmap(&mp.wq);
        prefetch_tmap(&mp.k);
        mbar_init(BAR(0), 1); mbar_init(BAR(22), 1); mbar_init(BAR(23), 1);
        asm volatile("fence.mbarrier_init.release.cluster;" ::: "memory");
        TL(32);
        if (is_att) {
#pragma unroll
            for (int h = 0; h < 2; ++h) {
                mbar_expect_tx(BAR(22 + h), HALF_BYTES);
                tma_2d(sb + OFF_WA + h * HALF_BYTES, &mp.wq, cta * 32, h * 288, BAR(22 + h));
                tma_2d(sb + OFF_WA + h * HALF_BYTES + HALF_BYTES / 2, &mp.wq, cta * 32, h * 288 + 144, BAR(22 + h));
            }
            mbar_expect_tx(BAR(0), SLOT_BYTES);
            tma_2d(sb, &mp.k, 0, kvline, BAR(0));
        }
        TL(33);
#pragma unroll
        for (int i = 1; i < NBAR; ++i)
            if (i != 22 && i != 23) mbar_init(BAR(i), 1);
        asm volatile("fence.mbarrier_init.release.cluster;" ::: "memory");
        prefetch_tmap(&mp.w1);
        prefetch_tmap(&mp.v);
        prefetch_tmap(&mp.w2);
        prefetch_tmap(&mp.wo);
    }
    if (tid == 0) TL(0);
    if (warp == 8) {
        __syncwarp();
        asm volatile("bar.arrive 0, 320;" ::: "memory");
        if (lane != 0) return;
        if (is_att) {
            int kv = 1, wi = 0;
            int phase = 0;
            uint32_t inflight = (1u << 22) | (1u << 23) | 1u;
#pragma unroll 1
            for (int n = 3; n < 24; ++n) {
                for (unsigned it = 0; it < SPIN_LIMIT; ++it) {
                    const int pace = phase == 0 ? PACE_A : (kv < 16 ? PACE : (phase == 1 ? PACE_END : PACE_FIN));
                    if (__popc(inflight) < pace) break;
                    for (uint32_t rem = inflight; rem; rem &= rem - 1) {
                        const int id = __ffs(rem) - 1;
                        if (mbar_test(BAR(BAR_FULL + id), 0)) inflight &= ~(1u << id);
                    }
                    if (phase < 2 && mbar_test(BAR(phase == 0 ? BAR_Q : BAR_O), 0)) ++phase;
                }
                bool take_kv = kv < 16;
                if (take_kv && kv >= NSLOT && !mbar_test(BAR(BAR_EMPTY + kv - NSLOT), 0)) {
                    if (wi < NFILL) take_kv = false;
                    else mbar_wait(BAR(BAR_EMPTY + kv - NSLOT), 0);
                }
                const int i = take_kv ? kv++ : 16 + wi++;
                TL(32 + n);
                inflight |= 1u << i;
                const uint32_t fb = BAR(BAR_FULL + i);
                const int h = i & 1;
                if (i == 20) mbar_wait(BAR(BAR_WQFREE), 0);
                mbar_expect_tx(fb, i < 16 ? SLOT_BYTES : HALF_BYTES);
                if (i < 16) {
                    tma_2d(sb + (i % NSLOT) * SLOT_BYTES, i < 8 ? &mp.k : &mp.v, 0, kvline + (i & 7) * 128, fb);
                } else if (i < 18) {
                    tma_2d(sb + OFF_WB + h * HALF_BYTES, &mp.w1, cta * 32, h * 288, fb);
                    tma_2d(sb + OFF_WB + h * HALF_BYTES + HALF_BYTES / 2, &mp.w1, cta * 32, h * 288 + 144, fb);
                } else {
                    tma_2d(sb + (i < 20 ? OFF_WC : OFF_WA) + h * HALF_BYTES, i < 20 ? &mp.w2 : &mp.wo, 0,
                           cta * 288 + h * 144, fb);
                }
            }
            TL(15);
        } else {
#pragma unroll 1
            for (int i = 0; i < 16; ++i) {
                if (i >= PACE) mbar_wait(BAR(BAR_FULL + i - PACE), 0);
                const uint32_t fb = BAR(BAR_FULL + i);
                const int u = (i >> 1) & 3, h = i & 1;
                if (i >= 8 && u > 0 && h == 0) mbar_wait(BAR(BAR_EMPTY + u - 1), 0);
                mbar_expect_tx(fb, HALF_BYTES);
                if (i < 8) {
                    tma_2d(sb + u * REG_BYTES + h * HALF_BYTES, &mp.w1, (funit + u) * 32, h * 288, fb);
                    tma_2d(sb + u * REG_BYTES + h * HALF_BYTES + HALF_BYTES / 2, &mp.w1, (funit + u) * 32, h * 288 + 144, fb);
                } else {
                    tma_2d(sb + (u == 0 ? 4 : u - 1) * REG_BYTES + h * HALF_BYTES, &mp.w2, 0, (funit + u) * 288 + h * 144, fb);
                }
            }
        }
        return;
    }

    uint32_t xw[9];
    unsigned short xres = 0;
    unsigned long long done0 = 0;
    if (warp < 4) {
        const uint32_t* xp = reinterpret_cast<const uint32_t*>(x) + warp * (DM / 2);
#pragma unroll
        for (int j = 0; j < 9; ++j) xw[j] = __ldg(xp + lane + 32 * j);
    }
    if (cta >= RED0 && warp == 0) {
        const int jr = cta - RED0, pc = lane >> 2, e = lane & 3;
        const int n = 16 * (jr >> 1) + (jr & 1) * 4 + (pc >> 1) + 8 * (e >> 1);
        const int b = 2 * (pc & 1) + (e & 1);
        xres = __ldg(reinterpret_cast<const unsigned short*>(x) + b * DM + n);
    }
    if (warp == 9 && cta >= RED0) done0 = ld_rlx64(&g_done);
    asm volatile("bar.sync 0, 320;" ::: "memory");

    if (warp == 9) {
        bool xchg = is_att;
        if (xchg) {
            mbar_wait(BAR(BAR_WQFREE), 0);
            {
                uint32_t* src = g_qbox + cta * 128 + lane * 4;
                uint4 v;
                for (unsigned it = 0; it < SPIN_LIMIT; ++it) {
                    v = ld_rlx4(src);
                    if (all_set(v)) break;
                }
                *reinterpret_cast<uint4*>(smem + OFF_Q + lane * 16) = v;
                __syncwarp();
                if (lane == 0) mbar_arrive(BAR(BAR_Q));
                st_rlx4(src, make_uint4(0, 0, 0, 0));
            }
            mbar_wait(BAR(BAR_FULL + 15), 0);
            uint32_t* s0 = g_obox + cta * 8 * 64;
            uint32_t* se = s0 + (lane >> 3) * 64 + 32 + (lane & 7);
            uint32_t v[8], e0 = 0, e1 = 0;
            for (unsigned it = 0; it < SPIN_LIMIT; ++it) {
#pragma unroll
                for (int i = 0; i < 8; ++i) v[i] = ld_rlx(s0 + i * 64 + lane);
                e0 = ld_rlx(se); e1 = ld_rlx(se + 4 * 64);
                bool ok = e0 && e1;
#pragma unroll
                for (int i = 0; i < 8; ++i) ok = ok && v[i];
                if (__all_sync(0xffffffffu, ok)) break;
            }
#pragma unroll
            for (int b = 0; b < 4; ++b) {
                const uint32_t e = b < 2 ? e0 : e1;
                const int sl = (b & 1) * 16;
                const float m0 = __uint_as_float(__shfl_sync(0xffffffffu, e, sl)), l0 = __uint_as_float(__shfl_sync(0xffffffffu, e, sl + 1));
                const float m1 = __uint_as_float(__shfl_sync(0xffffffffu, e, sl + 8)), l1 = __uint_as_float(__shfl_sync(0xffffffffu, e, sl + 9));
                const float M = fmaxf(m0, m1);
                const float f0 = exp2f(m0 - M), f1 = exp2f(m1 - M);
                const float o = __fdividef(__uint_as_float(v[2 * b]) * f0 + __uint_as_float(v[2 * b + 1]) * f1, l0 * f0 + l1 * f1);
                reinterpret_cast<__nv_bfloat16*>(smem + OFF_O)[b * APITCH + lane] = __float2bfloat16_rn(o);
            }
            __syncwarp();
            if (lane == 0) mbar_arrive(BAR(BAR_O));
            if (lane == 0) TL(14);
#pragma unroll
            for (int i = 0; i < 8; ++i) st_rlx(s0 + i * 64 + lane, 0);
            st_rlx(se, 0); st_rlx(se + 4 * 64, 0);
        }
        if (cta >= RED0 && lane == 0) {
            const unsigned long long target = (done0 / NCTA + 1) * NCTA;
            bool first = false;
            for (unsigned it = 0; it < SPIN_LIMIT; ++it) {
                const unsigned long long d = ld_rlx64(&g_done);
                if (!first && d + TRIG1 >= target) { first = true; mbar_arrive(BAR(BAR_GO1)); }
                if (d >= target) break;
                if (!first) __nanosleep(100);
            }
            if (!first) mbar_arrive(BAR(BAR_GO1));
            mbar_arrive(BAR(BAR_GO));
        }
        return;
    }

    const int g = lane >> 2, t = lane & 3;
    float* red = reinterpret_cast<float*>(smem + OFF_RED);

    if (warp < 4) {
        float s = 0.f;
#pragma unroll
        for (int j = 0; j < 9; ++j) s += bf_lo(xw[j]) + bf_hi(xw[j]);
#pragma unroll
        for (int o = 16; o; o >>= 1) s += __shfl_xor_sync(0xffffffffu, s, o);
        const float mean = s * (1.f / DM);
        float v = 0.f;
#pragma unroll
        for (int j = 0; j < 9; ++j) {
            float a = bf_lo(xw[j]) - mean, c = bf_hi(xw[j]) - mean;
            v += a * a + c * c;
        }
#pragma unroll
        for (int o = 16; o; o >>= 1) v += __shfl_xor_sync(0xffffffffu, v, o);
        const float mb = bf16r(mean);
        const float rden = 1.f / bf16r(sqrtf(bf16r(bf16r(v * (1.f / DM)) + 1e-5f)));
        uint32_t* xs = reinterpret_cast<uint32_t*>(smem + OFF_XN + warp * XPITCH * 2);
#pragma unroll
        for (int j = 0; j < 9; ++j)
            xs[lane + 32 * j] = pack_bf16(bf16r(bf_lo(xw[j]) - mb) * rden, bf16r(bf_hi(xw[j]) - mb) * rden);
    }
    cbar();

    float acc[5][4] = {};

    if (is_att) {
        mbar_wait(BAR(BAR_FULL + 22 + (warp >> 2)), 0);
        if (tid == 0) TL(1);
        col_gemv(sb + OFF_WA, sb + OFF_XN, red, warp, lane);
        cbar();
        if (tid < 64) {
            const int b = tid >> 4, pr = tid & 15;
            float v0 = 0.f, v1 = 0.f;
#pragma unroll
            for (int kg = 0; kg < 4; ++kg) {
                v0 += red[(kg * 32 + 2 * pr) * 4 + b];
                v1 += red[(kg * 32 + 2 * pr + 1) * 4 + b];
            }
            const uint32_t w = enc(pack_bf16(v0, v1));
            uint32_t* dst = g_qbox + (kvh * 8 + 2 * b) * 128 + rk * 16 + pr;
            st_rlx(dst, w);
            st_rlx(dst + 128, w);
        }
        if (tid == 0) { mbar_arrive(BAR(BAR_WQFREE)); TL(2); }
        mbar_wait(BAR(BAR_Q), 0);
        if (tid == 0) TL(3);

        uint4 qa[4];
#pragma unroll
        for (int j = 0; j < 4; ++j) {
            qa[j] = lds128(sb + OFF_Q + (g & 1) * 256 + j * 64 + t * 16);
            if (g >= 2) qa[j] = make_uint4(0, 0, 0, 0);
        }
        float s[8][2];
        {
            const int f = (g >> 1) ^ (2 * (g & 1));
            const uint32_t kb = sb + (warp % NSLOT) * SLOT_BYTES + (4 * (g & 1) + f) * 256;
            uint32_t ko[4];
#pragma unroll
            for (int j = 0; j < 4; ++j) ko[j] = kb + (j >> 1) * 128 + (((4 * (j & 1) + t) ^ (2 * f + (j >> 1))) << 4);
            mbar_wait(BAR(BAR_FULL + warp), 0);
#pragma unroll
            for (int T = 0; T < 8; ++T) {
                float c[4] = {0.f, 0.f, 0.f, 0.f};
#pragma unroll
                for (int j = 0; j < 4; ++j) {
                    const uint4 kv = lds128(ko[j] + T * 2048);
                    mma16816(c, qa[j].x, 0u, qa[j].y, 0u, kv.x, kv.y);
                    mma16816(c, qa[j].z, 0u, qa[j].w, 0u, kv.z, kv.w);
                }
                s[T][0] = c[0];
                s[T][1] = c[1];
            }
            __syncwarp();
            if (lane == 0) mbar_arrive(BAR(BAR_EMPTY + warp));
        }
        if (lane == 0 && (warp == 0 || warp == 7)) TL(warp == 0 ? 4 : 5);
        const float cs = 0.08838834764831845f * 1.4426950408889634f;
        float m = s[0][0];
#pragma unroll
        for (int T = 0; T < 8; ++T) m = fmaxf(m, fmaxf(s[T][0], s[T][1]));
        m = fmaxf(m, __shfl_xor_sync(0xffffffffu, m, 1));
        m = fmaxf(m, __shfl_xor_sync(0xffffffffu, m, 2));
        const float mc = m * cs;
        float l = 0.f;
        uint32_t pb[8];
#pragma unroll
        for (int T = 0; T < 8; ++T) {
            const float p0 = exp2f(fmaf(s[T][0], cs, -mc)), p1 = exp2f(fmaf(s[T][1], cs, -mc));
            l += p0 + p1;
            pb[T] = pack_bf16(p0, p1);
        }
        l += __shfl_xor_sync(0xffffffffu, l, 1);
        l += __shfl_xor_sync(0xffffffffu, l, 2);
        float2* ml = reinterpret_cast<float2*>(smem + OFF_ML);
        if (g < 2 && t == 0) ml[warp * 2 + g] = make_float2(mc, l);

        {
            const int c = 8 + warp;
            const uint32_t vb = sb + (c % NSLOT) * SLOT_BYTES;
            uint32_t vo[2][2];
#pragma unroll
            for (int e = 0; e < 2; ++e)
#pragma unroll
                for (int hf = 0; hf < 2; ++hf) {
                    const int f = t ^ (2 * e);
                    vo[e][hf] = vb + (4 * e + f) * 256 + hf * 128 + ((g ^ (2 * f + hf)) << 4);
                }
            mbar_wait(BAR(BAR_FULL + c), 0);
            float o[2][4][4] = {};
#pragma unroll
            for (int ks = 0; ks < 4; ++ks) {
#pragma unroll
                for (int hf = 0; hf < 2; ++hf) {
                    const uint4 R0 = lds128(vo[0][hf] + ks * 4096), R1 = lds128(vo[1][hf] + ks * 4096);
                    const uint4 R2 = lds128(vo[0][hf] + ks * 4096 + 2048), R3 = lds128(vo[1][hf] + ks * 4096 + 2048);
                    const uint32_t r0[4] = {R0.x, R0.y, R0.z, R0.w}, r1[4] = {R1.x, R1.y, R1.z, R1.w};
                    const uint32_t r2[4] = {R2.x, R2.y, R2.z, R2.w}, r3[4] = {R3.x, R3.y, R3.z, R3.w};
#pragma unroll
                    for (int j = 0; j < 4; ++j)
                        mma16816(o[hf][j], __byte_perm(r0[j], r1[j], 0x5410), __byte_perm(r0[j], r1[j], 0x7632),
                                 __byte_perm(r2[j], r3[j], 0x5410), __byte_perm(r2[j], r3[j], 0x7632),
                                 pb[2 * ks], pb[2 * ks + 1]);
                }
            }
            __syncwarp();
            if (lane == 0 && c + NSLOT < 16) mbar_arrive(BAR(BAR_EMPTY + c));
            if (t == 0) {
                float* op = reinterpret_cast<float*>(smem + OFF_OP) + warp * 256 + 8 * g;
#pragma unroll
                for (int hf = 0; hf < 2; ++hf)
#pragma unroll
                    for (int jp = 0; jp < 2; ++jp) {
                        *reinterpret_cast<float4*>(op + 64 * hf + 4 * jp) =
                            make_float4(o[hf][2 * jp][0], o[hf][2 * jp][2], o[hf][2 * jp + 1][0], o[hf][2 * jp + 1][2]);
                        *reinterpret_cast<float4*>(op + 128 + 64 * hf + 4 * jp) =
                            make_float4(o[hf][2 * jp][1], o[hf][2 * jp][3], o[hf][2 * jp + 1][1], o[hf][2 * jp + 1][3]);
                    }
            }
        }
        cbar();
        if (tid == 0) TL(6);
        {
            const int head = tid >> 7;
            float M = ml[head].x;
#pragma unroll
            for (int w = 1; w < 8; ++w) M = fmaxf(M, ml[w * 2 + head].x);
            const float* op = reinterpret_cast<const float*>(smem + OFF_OP) + tid;
            float o = 0.f, L = 0.f;
#pragma unroll
            for (int w = 0; w < 8; ++w) {
                const float2 e = ml[w * 2 + head];
                const float f = exp2f(e.x - M);
                o = fmaf(f, op[w * 256], o);
                L = fmaf(f, e.y, L);
            }
            uint32_t* dst = g_obox + ((kvh * 8 + warp) * 8 + rk) * 64;
            st_rlx(dst + lane, encf(o));
            if (lane < 8) st_rlx(dst + 32 + lane, encf((lane & 1) ? L : M));
        }
        if (tid == 0) TL(7);
    }

    const int nu = is_att ? 1 : 4;
#pragma unroll 1
    for (int u = 0; u < nu; ++u) {
        float bias = 0.f;
        if (tid < 128) bias = __bfloat162float(b1[(funit + u) * 32 + (tid >> 2)]);
        mbar_wait(BAR(BAR_FULL + (is_att ? 16 : 2 * u) + (warp >> 2)), 0);
        if (tid == 0) TL(8);
        col_gemv(sb + (is_att ? OFF_WB : u * REG_BYTES), sb + OFF_XN, red, warp, lane);
        cbar();
        if (tid == 0 && u < nu - 1) mbar_arrive(BAR(BAR_EMPTY + u));
        if (tid < 128) {
            float h = red[tid] + red[128 + tid] + red[256 + tid] + red[384 + tid];
            h = bf16r(bf16r(h) + bias);
            reinterpret_cast<__nv_bfloat16*>(smem + OFF_ACT + u * 320)[(tid & 3) * APITCH + (tid >> 2)] =
                __float2bfloat16_rn(mish(h));
        }
        cbar();
    }
    if (tid == 0) TL(9);

    const int nr = is_att ? 4 : 8;
#pragma unroll 1
    for (int i = 0; i < nr; ++i) {
        const int u = i >> 1, h = i & 1;
        if (is_att && i == 2) mbar_wait(BAR(BAR_O), 0);
        mbar_wait(BAR(BAR_FULL + (is_att ? 18 : 8) + i), 0);
        if (tid == 0 && i == nr - 1) red_add64(&g_done, 1);
        if (tid == 0 && (i == 0 || i == nr - 1)) TL(i == 0 ? 10 : 11);
        const uint32_t wbase = is_att ? (u ? OFF_WA : OFF_WC) : (u == 0 ? 4 : u - 1) * REG_BYTES;
        const uint32_t vbase = is_att ? (u ? OFF_O : OFF_ACT) : OFF_ACT + u * 320;
        row_gemv16(sb + wbase + h * HALF_BYTES, sb + vbase + h * 32, acc, warp, lane);
    }

    if (t < 2) {
#pragma unroll
        for (int i = 0; i < 5; ++i) {
            if (i < 4 || warp < 4) {
                const int jr = 2 * (warp + 8 * i) + (g >> 2);
                uint32_t* dst = g_part + ((size_t)(jr * NCTA + cta) * 32 + ((g & 3) * 2 + t) * 4);
                st_rlx4(dst, make_uint4(encf(acc[i][0]), encf(acc[i][1]), encf(acc[i][2]), encf(acc[i][3])));
            }
        }
    }
    if (tid == 0) TL(12);

    if (cta >= RED0) {
        const int jr = cta - RED0;
        const int p0 = (lane >> 3) + 4 * warp;
        uint32_t* src = g_part + ((size_t)(jr * NCTA + p0) * 32 + (lane & 7) * 4);
        uint4 v[5];
        const bool has4 = p0 + 128 < NCTA;
        unsigned pend = has4 ? 31u : 15u;
        v[4] = make_uint4(0, 0, 0, 0);
        mbar_wait(BAR(BAR_GO1), 0);
        for (unsigned it = 0; it < SPIN_LIMIT; ++it) {
#pragma unroll
            for (int i = 0; i < 5; ++i)
                if (pend & (1u << i)) v[i] = ld_rlx4(src + i * 32 * 32);
#pragma unroll
            for (int i = 0; i < 5; ++i)
                if ((pend & (1u << i)) && all_set(v[i])) pend &= ~(1u << i);
            if (!pend) break;
            if (it == 0) mbar_wait(BAR(BAR_GO), 0);
        }
        float4 a = make_float4(0.f, 0.f, 0.f, 0.f);
#pragma unroll
        for (int i = 0; i < 5; ++i) {
            a.x += __uint_as_float(v[i].x); a.y += __uint_as_float(v[i].y);
            a.z += __uint_as_float(v[i].z); a.w += __uint_as_float(v[i].w);
        }
#pragma unroll
        for (int o = 8; o <= 16; o <<= 1) {
            a.x += __shfl_xor_sync(0xffffffffu, a.x, o); a.y += __shfl_xor_sync(0xffffffffu, a.y, o);
            a.z += __shfl_xor_sync(0xffffffffu, a.z, o); a.w += __shfl_xor_sync(0xffffffffu, a.w, o);
        }
        if (lane < 8) *reinterpret_cast<float4*>(red + warp * 32 + lane * 4) = a;
        cbar();
        if (tid < 32) {
            float r = __uint_as_float((uint32_t)xres << 16);
#pragma unroll
            for (int w = 0; w < 8; ++w) r += red[w * 32 + tid];
            const int pc = tid >> 2, e = tid & 3;
            const int n = 16 * (jr >> 1) + (jr & 1) * 4 + (pc >> 1) + 8 * (e >> 1);
            const int b = 2 * (pc & 1) + (e & 1);
            out[b * DM + n] = __float2bfloat16_rn(r);
        }
        if (tid == 0) TL(13);
#pragma unroll
        for (int i = 0; i < 5; ++i)
            if (i < 4 || has4) st_rlx4(src + i * 32 * 32, make_uint4(0, 0, 0, 0));
    }
}

__device__ void fb_layernorm(const __nv_bfloat16* x, float* xn  ) {
    const int warp = threadIdx.x >> 5, lane = threadIdx.x & 31;
    if (warp < NB) {
        float s = 0.f;
        for (int i = lane; i < DM; i += 32) s += __bfloat162float(x[warp * DM + i]);
        for (int o = 16; o; o >>= 1) s += __shfl_xor_sync(0xffffffffu, s, o);
        const float mean = s / DM;
        float v = 0.f;
        for (int i = lane; i < DM; i += 32) { float d = __bfloat162float(x[warp * DM + i]) - mean; v += d * d; }
        for (int o = 16; o; o >>= 1) v += __shfl_xor_sync(0xffffffffu, v, o);
        const float mb = bf16r(mean);
        const float den = bf16r(sqrtf(bf16r(bf16r(v / DM) + 1e-5f)));
        for (int i = lane; i < DM; i += 32)
            xn[warp * DM + i] = bf16r(bf16r(__bfloat162float(x[warp * DM + i]) - mb) / den);
    }
    __syncthreads();
}

__global__ void fb_proj(const __nv_bfloat16* x, const __nv_bfloat16* wq, const __nv_bfloat16* w1,
                        const __nv_bfloat16* b1) {
    __shared__ float xn[NB * DM];
    fb_layernorm(x, xn);
    const int c = blockIdx.x * blockDim.x + threadIdx.x;
    if (c >= QD + FF) return;
    const bool isq = c < QD;
    const __nv_bfloat16* w = isq ? wq + c : w1 + (c - QD);
    const int pitch = isq ? QD : FF;
    float a[NB] = {};
    for (int k = 0; k < DM; ++k) {
        const float wv = __bfloat162float(w[(size_t)k * pitch]);
        for (int b = 0; b < NB; ++b) a[b] = fmaf(xn[b * DM + k], wv, a[b]);
    }
    for (int b = 0; b < NB; ++b) {
        if (isq) g_fb_q[b * QD + c] = __float2bfloat16_rn(a[b]);
        else {
            const float h = bf16r(bf16r(a[b]) + __bfloat162float(b1[c - QD]));
            g_fb_act[b * FF + c - QD] = __float2bfloat16_rn(mish(h));
        }
    }
}

__global__ void fb_attn(const __nv_bfloat16* kc, const __nv_bfloat16* vc) {
    __shared__ float q[DH], p[WIN], rd[128];
    const int b = blockIdx.x / HQ, h = blockIdx.x % HQ, tid = threadIdx.x;
    const size_t base = ((size_t)(b * HKV + h / 2) * SK + (SK - WIN)) * DH;
    q[tid] = __bfloat162float(g_fb_q[b * QD + h * DH + tid]);
    __syncthreads();
    float m = -INFINITY;
    for (int k = tid; k < WIN; k += 128) {
        float s = 0.f;
        for (int d = 0; d < DH; ++d) s = fmaf(q[d], __bfloat162float(kc[base + (size_t)k * DH + d]), s);
        s *= 0.08838834764831845f;
        p[k] = s;
        m = fmaxf(m, s);
    }
    rd[tid] = m;
    __syncthreads();
    for (int i = 0; i < 128; ++i) m = fmaxf(m, rd[i]);
    __syncthreads();
    float l = 0.f;
    for (int k = tid; k < WIN; k += 128) { p[k] = expf(p[k] - m); l += p[k]; }
    rd[tid] = l;
    __syncthreads();
    l = 0.f;
    for (int i = 0; i < 128; ++i) l += rd[i];
    float o = 0.f;
    for (int k = 0; k < WIN; ++k) o = fmaf(p[k], __bfloat162float(vc[base + (size_t)k * DH + tid]), o);
    g_fb_o[b * QD + h * DH + tid] = __float2bfloat16_rn(o / l);
}

__global__ void fb_out(const __nv_bfloat16* x, const __nv_bfloat16* wo, const __nv_bfloat16* w2,
                       __nv_bfloat16* out) {
    __shared__ float rd[8][NB][32];
    const int n = blockIdx.x * 32 + (threadIdx.x & 31), part = threadIdx.x >> 5;
    float a[NB] = {};
    for (int k = part; k < QD; k += 8) {
        const float wv = __bfloat162float(wo[(size_t)k * DM + n]);
        for (int b = 0; b < NB; ++b) a[b] = fmaf(__bfloat162float(g_fb_o[b * QD + k]), wv, a[b]);
    }
    for (int k = part; k < FF; k += 8) {
        const float wv = __bfloat162float(w2[(size_t)k * DM + n]);
        for (int b = 0; b < NB; ++b) a[b] = fmaf(__bfloat162float(g_fb_act[b * FF + k]), wv, a[b]);
    }
    for (int b = 0; b < NB; ++b) rd[part][b][threadIdx.x & 31] = a[b];
    __syncthreads();
    if (threadIdx.x < 128) {
        const int b = threadIdx.x >> 5, c = threadIdx.x & 31;
        float r = __bfloat162float(x[b * DM + blockIdx.x * 32 + c]);
        for (int i = 0; i < 8; ++i) r += rd[i][b][c];
        out[b * DM + blockIdx.x * 32 + c] = __float2bfloat16_rn(r);
    }
}

void launch_fallback(const __nv_bfloat16* x, const __nv_bfloat16* kc, const __nv_bfloat16* vc,
                     const __nv_bfloat16* wq, const __nv_bfloat16* wo, const __nv_bfloat16* w1,
                     const __nv_bfloat16* b1, const __nv_bfloat16* w2, __nv_bfloat16* out) {
    fb_proj<<<(QD + FF) / 128, 128>>>(x, wq, w1, b1);
    fb_attn<<<NB * HQ, 128>>>(kc, vc);
    fb_out<<<DM / 32, 256>>>(x, wo, w2, out);
}

typedef CUresult (*EncodeFn)(CUtensorMap*, CUtensorMapDataType, cuuint32_t, void*, const cuuint64_t*, const cuuint64_t*,
                             const cuuint32_t*, const cuuint32_t*, CUtensorMapInterleave, CUtensorMapSwizzle,
                             CUtensorMapL2promotion, CUtensorMapFloatOOBfill);

#define L2PROMO CU_TENSOR_MAP_L2_PROMOTION_L2_128B

bool make_map(EncodeFn fn, CUtensorMap* m, const void* base, uint64_t cols, uint64_t rows, uint32_t box_cols,
              uint32_t box_rows, CUtensorMapSwizzle sw) {
    cuuint64_t dims[2] = {cols, rows};
    cuuint64_t strides[1] = {cols * 2};
    cuuint32_t box[2] = {box_cols, box_rows};
    cuuint32_t es[2] = {1, 1};
    return fn(m, CU_TENSOR_MAP_DATA_TYPE_BFLOAT16, 2, const_cast<void*>(base), dims, strides, box, es,
              CU_TENSOR_MAP_INTERLEAVE_NONE, sw, L2PROMO, CU_TENSOR_MAP_FLOAT_OOB_FILL_NONE) == CUDA_SUCCESS;
}

struct HostState {
    int ok;
    EncodeFn encode;
    const void* ptr[6];
    bool maps_ok;
    Maps maps;
};
HostState g_host = {-1, nullptr, {nullptr, nullptr, nullptr, nullptr, nullptr, nullptr}, false, {}};

bool fused_ready(const void* wq, const void* kc, const void* vc, const void* w1, const void* w2, const void* wo) {
    HostState& h = g_host;
    if (h.ok < 0) {
        int dev = 0, sms = 0, occ = 0;
        void* fn = nullptr;
        cudaDriverEntryPointQueryResult qr;
        h.ok = 0;
        if (cudaGetDevice(&dev) == cudaSuccess &&
            cudaDeviceGetAttribute(&sms, cudaDevAttrMultiProcessorCount, dev) == cudaSuccess &&
            cudaFuncSetAttribute(fused_kernel, cudaFuncAttributeMaxDynamicSharedMemorySize, SMEM_BYTES) == cudaSuccess &&
            cudaOccupancyMaxActiveBlocksPerMultiprocessor(&occ, fused_kernel, NTHREADS, SMEM_BYTES) == cudaSuccess &&
            sms * occ >= NCTA &&
            cudaGetDriverEntryPoint("cuTensorMapEncodeTiled", &fn, cudaEnableDefault, &qr) == cudaSuccess &&
            qr == cudaDriverEntryPointSuccess && fn) {
            h.encode = (EncodeFn)fn;
            h.ok = 1;
        }
        (void)cudaGetLastError();
    }
    if (h.ok != 1) return false;
    const void* p[6] = {wq, kc, vc, w1, w2, wo};
    bool same = true;
    for (int i = 0; i < 6; ++i) same = same && h.ptr[i] == p[i];
    if (!same) {
        for (int i = 0; i < 6; ++i) h.ptr[i] = p[i];
        const uint64_t kvlines = (uint64_t)NB * HKV * SK * DH / 64;
        h.maps_ok = make_map(h.encode, &h.maps.wq, wq, QD, DM, 32, 144, CU_TENSOR_MAP_SWIZZLE_64B) &&
                    make_map(h.encode, &h.maps.w1, w1, FF, DM, 32, 144, CU_TENSOR_MAP_SWIZZLE_64B) &&
                    make_map(h.encode, &h.maps.k, kc, 64, kvlines, 64, 128, CU_TENSOR_MAP_SWIZZLE_128B) &&
                    make_map(h.encode, &h.maps.v, vc, 64, kvlines, 64, 128, CU_TENSOR_MAP_SWIZZLE_128B) &&
                    make_map(h.encode, &h.maps.w2, w2, 64, (uint64_t)FF * DM / 64, 64, 144, CU_TENSOR_MAP_SWIZZLE_128B) &&
                    make_map(h.encode, &h.maps.wo, wo, 64, (uint64_t)QD * DM / 64, 64, 144, CU_TENSOR_MAP_SWIZZLE_128B);
    }
    return h.maps_ok;
}

}

extern "C" void kernel_launch(void* const* d_in, const int* in_sizes, int n_in, void* d_out, int out_size) {
    const __nv_bfloat16* x = (const __nv_bfloat16*)d_in[0];
    const __nv_bfloat16* kc = (const __nv_bfloat16*)d_in[1];
    const __nv_bfloat16* vc = (const __nv_bfloat16*)d_in[2];
    const __nv_bfloat16* wq = (const __nv_bfloat16*)d_in[3];
    const __nv_bfloat16* wo = (const __nv_bfloat16*)d_in[4];
    const __nv_bfloat16* w1 = (const __nv_bfloat16*)d_in[6];
    const __nv_bfloat16* b1 = (const __nv_bfloat16*)d_in[7];
    const __nv_bfloat16* w2 = (const __nv_bfloat16*)d_in[8];
    __nv_bfloat16* out = (__nv_bfloat16*)d_out;
    if (fused_ready(wq, kc, vc, w1, w2, wo))
        fused_kernel<<<NCTA, NTHREADS, SMEM_BYTES>>>(g_host.maps, x, b1, out);
    else
        launch_fallback(x, kc, vc, wq, wo, w1, b1, w2, out);
}
```

```cpp
#include <cuda_runtime.h>
#include <cuda.h>
#include <cuda_bf16.h>
#include <stdint.h>

#define DEVINL __device__ __forceinline__

namespace {

constexpr int NB = 4;
constexpr int DM = 576;
constexpr int HQ = 32, HKV = 16, SK = 4096, DH = 128, WIN = 1024;
constexpr int FF = 4608;
constexpr int QD = HQ * DH;

constexpr int NATT = 128;
constexpr int NCTA = 132;
constexpr int NRED = 72;
constexpr int RED0 = NCTA - NRED;
constexpr int NTHREADS = 352;

constexpr int SLOT_BYTES = 16384;
constexpr int NSLOT = 6;
constexpr int REG_BYTES = 36864;
constexpr int HALF_BYTES = REG_BYTES / 2;
constexpr int OFF_WA = NSLOT * SLOT_BYTES;
constexpr int OFF_WB = OFF_WA + REG_BYTES;
constexpr int OFF_WC = OFF_WB + REG_BYTES;
constexpr int OFF_MISC = OFF_WC + REG_BYTES;
constexpr int XPITCH = 584;
constexpr int OFF_XN = OFF_MISC;
constexpr int OFF_RED = OFF_XN + NB * XPITCH * 2;
constexpr int OFF_Q = OFF_RED + 2048;
constexpr int OFF_ACT = OFF_Q + 512;
constexpr int OFF_O = OFF_ACT + 1280;
constexpr int OFF_ML = OFF_O + 320;
constexpr int OFF_BAR = OFF_ML + 128;
constexpr int OFF_OP = OFF_BAR + 352;
constexpr int SMEM_BYTES = OFF_OP + 8192;
static_assert(SMEM_BYTES <= 232448, "smem");
static_assert(OFF_RED % 16 == 0 && OFF_Q % 16 == 0 && OFF_OP % 16 == 0 && OFF_BAR % 8 == 0, "align");
static_assert(5 * REG_BYTES <= OFF_MISC, "ffn cta regions");
static_assert(OFF_WA % 1024 == 0 && HALF_BYTES % 1024 == 0, "swizzle atom alignment");

constexpr int APITCH = 40;

constexpr int BAR_FULL = 0;
constexpr int BAR_EMPTY = 24;
constexpr int BAR_WQFREE = 34, BAR_Q = 35, BAR_O = 36, BAR_EP = 37, NBAR = 38;

#define PACE_A 3
#define PACE 4
#define PACE_END 2
#define PACE_FIN 3
#define NFILL 2
#define BAL_UP 64
#define BAL_DN 96
#define BAL_SLEEP 100

constexpr unsigned SPIN_LIMIT = 1u << 20;

__device__ uint32_t g_qbox[NATT * 256];
__device__ uint32_t g_obox[NATT * 8 * 64];
__device__ uint32_t g_part[NRED * NCTA * 32];
__device__ uint32_t g_cnt[NATT * 32];
__device__ unsigned long long g_prog;
__device__ unsigned long long g_done;

__device__ __nv_bfloat16 g_fb_q[NB * QD];
__device__ __nv_bfloat16 g_fb_act[NB * FF];
__device__ __nv_bfloat16 g_fb_o[NB * QD];

#define TL(i) do {} while (0)

DEVINL uint32_t smem_u32(const void* p) { return (uint32_t)__cvta_generic_to_shared(p); }

DEVINL void mbar_init(uint32_t bar, uint32_t cnt) {
    asm volatile("mbarrier.init.shared::cta.b64 [%0], %1;" ::"r"(bar), "r"(cnt) : "memory");
}
DEVINL void mbar_expect_tx(uint32_t bar, uint32_t bytes) {
    asm volatile("mbarrier.arrive.expect_tx.shared::cta.b64 _, [%0], %1;" ::"r"(bar), "r"(bytes) : "memory");
}
DEVINL void mbar_arrive(uint32_t bar) {
    asm volatile("mbarrier.arrive.shared::cta.b64 _, [%0];" ::"r"(bar) : "memory");
}
DEVINL void mbar_wait(uint32_t bar, uint32_t parity) {
    uint32_t ok = 0;
    for (unsigned it = 0; it < SPIN_LIMIT; ++it) {
        asm volatile(
            "{\n\t.reg .pred p;\n\t"
            "mbarrier.try_wait.parity.shared::cta.b64 p, [%1], %2;\n\t"
            "selp.u32 %0, 1, 0, p;\n\t}"
            : "=r"(ok) : "r"(bar), "r"(parity) : "memory");
        if (ok) break;
    }
}
DEVINL bool mbar_test(uint32_t bar, uint32_t parity) {
    uint32_t ok;
    asm volatile(
        "{\n\t.reg .pred p;\n\t"
        "mbarrier.test_wait.parity.shared::cta.b64 p, [%1], %2;\n\t"
        "selp.u32 %0, 1, 0, p;\n\t}"
        : "=r"(ok) : "r"(bar), "r"(parity) : "memory");
    return ok != 0;
}
DEVINL void tma_2d(uint32_t dst, const CUtensorMap* map, int c0, int c1, uint32_t bar) {
    asm volatile(
        "cp.async.bulk.tensor.2d.shared::cluster.global.mbarrier::complete_tx::bytes.L2::cache_hint [%0], [%1, {%2, %3}], [%4], %5;"
        ::"r"(dst), "l"(map), "r"(c0), "r"(c1), "r"(bar), "l"(0x12F0000000000000ull) : "memory");
}
DEVINL void tma_2d_keep(uint32_t dst, const CUtensorMap* map, int c0, int c1, uint32_t bar) {
    asm volatile(
        "cp.async.bulk.tensor.2d.shared::cluster.global.mbarrier::complete_tx::bytes [%0], [%1, {%2, %3}], [%4];"
        ::"r"(dst), "l"(map), "r"(c0), "r"(c1), "r"(bar) : "memory");
}
DEVINL void prefetch_tmap(const CUtensorMap* map) {
    asm volatile("prefetch.tensormap [%0];" ::"l"(map) : "memory");
}
DEVINL void cbar() { asm volatile("bar.sync 1, 256;" ::: "memory"); }

DEVINL void ldsm4t(uint32_t addr, uint32_t& r0, uint32_t& r1, uint32_t& r2, uint32_t& r3) {
    asm volatile("ldmatrix.sync.aligned.m8n8.x4.trans.shared.b16 {%0,%1,%2,%3}, [%4];"
                 : "=r"(r0), "=r"(r1), "=r"(r2), "=r"(r3) : "r"(addr) : "memory");
}
DEVINL uint4 lds128(uint32_t addr) {
    uint4 v;
    asm volatile("ld.shared.v4.u32 {%0,%1,%2,%3}, [%4];" : "=r"(v.x), "=r"(v.y), "=r"(v.z), "=r"(v.w) : "r"(addr) : "memory");
    return v;
}
DEVINL uint32_t lds32(uint32_t addr) {
    uint32_t v;
    asm volatile("ld.shared.u32 %0, [%1];" : "=r"(v) : "r"(addr) : "memory");
    return v;
}
DEVINL void mma16816(float* c, uint32_t a0, uint32_t a1, uint32_t a2, uint32_t a3, uint32_t b0, uint32_t b1) {
    asm volatile(
        "mma.sync.aligned.m16n8k16.row.col.f32.bf16.bf16.f32 {%0,%1,%2,%3}, {%4,%5,%6,%7}, {%8,%9}, {%0,%1,%2,%3};"
        : "+f"(c[0]), "+f"(c[1]), "+f"(c[2]), "+f"(c[3])
        : "r"(a0), "r"(a1), "r"(a2), "r"(a3), "r"(b0), "r"(b1));
}
DEVINL uint32_t pack_bf16(float lo, float hi) {
    uint32_t r;
    asm("cvt.rn.bf16x2.f32 %0, %1, %2;" : "=r"(r) : "f"(hi), "f"(lo));
    return r;
}
DEVINL float bf16r(float x) { return __bfloat162float(__float2bfloat16_rn(x)); }
DEVINL float bf_lo(uint32_t w) { return __uint_as_float(w << 16); }
DEVINL float bf_hi(uint32_t w) { return __uint_as_float(w & 0xffff0000u); }

DEVINL uint32_t encf(float f, uint32_t ep) { return (__float_as_uint(f) & ~3u) | ep; }
DEVINL bool tag_ok(uint32_t w, uint32_t ep) { return (w & 3u) == ep; }
DEVINL void st_rlx(uint32_t* p, uint32_t v) {
    asm volatile("st.relaxed.gpu.global.u32 [%0], %1;" ::"l"(p), "r"(v) : "memory");
}
DEVINL void st_rlx4(uint32_t* p, uint4 v) {
    asm volatile("st.relaxed.gpu.global.v4.u32 [%0], {%1,%2,%3,%4};" ::"l"(p), "r"(v.x), "r"(v.y), "r"(v.z), "r"(v.w) : "memory");
}
DEVINL uint32_t ld_rlx(const uint32_t* p) {
    uint32_t v;
    asm volatile("ld.relaxed.gpu.global.u32 %0, [%1];" : "=r"(v) : "l"(p) : "memory");
    return v;
}
DEVINL uint4 ld_rlx4(const uint32_t* p) {
    uint4 v;
    asm volatile("ld.relaxed.gpu.global.v4.u32 {%0,%1,%2,%3}, [%4];" : "=r"(v.x), "=r"(v.y), "=r"(v.z), "=r"(v.w) : "l"(p) : "memory");
    return v;
}
DEVINL unsigned long long ld_rlx64(const unsigned long long* p) {
    unsigned long long v;
    asm volatile("ld.relaxed.gpu.global.u64 %0, [%1];" : "=l"(v) : "l"(p) : "memory");
    return v;
}
DEVINL void red_add64(unsigned long long* p, unsigned long long v) {
    asm volatile("red.relaxed.gpu.global.add.u64 [%0], %1;" ::"l"(p), "l"(v) : "memory");
}
DEVINL void red_add32(uint32_t* p, uint32_t v) {
    asm volatile("red.relaxed.gpu.global.add.u32 [%0], %1;" ::"l"(p), "r"(v) : "memory");
}
DEVINL void wait_count(const uint32_t* p, uint32_t target) {
    for (unsigned it = 0; it < SPIN_LIMIT; ++it)
        if ((int)(ld_rlx(p) - target) >= 0) break;
}
DEVINL bool all_set(uint4 v, uint32_t ep) { return (((v.x ^ ep) | (v.y ^ ep) | (v.z ^ ep) | (v.w ^ ep)) & 3u) == 0; }

DEVINL float mish(float h) {
    float sp = log1pf(expf(-fabsf(h))) + fmaxf(h, 0.f);
    return h * tanhf(sp);
}

DEVINL void col_gemv(uint32_t wbase, uint32_t xn_s, float* red, int warp, int lane) {
    const int mt = warp & 1, kg = warp >> 1;
    const int g = lane >> 2, t = lane & 3;
    const int j = lane >> 3, r = lane & 7;
    const int chunk = 2 * mt + (j & 1);
    const uint32_t aaddr = wbase + (kg * 144 + (j >> 1) * 8 + r) * 64 + ((chunk ^ ((r >> 1) & 3)) << 4);
    const uint32_t baddr = xn_s + ((g & 3) * XPITCH + kg * 144 + 2 * t) * 2;
    float acc[3][4] = {};
#pragma unroll
    for (int ks = 0; ks < 9; ++ks) {
        uint32_t a0, a1, a2, a3;
        ldsm4t(aaddr + ks * 1024, a0, a1, a2, a3);
        uint32_t b0 = lds32(baddr + ks * 32), b1 = lds32(baddr + ks * 32 + 16);
        if (g >= 4) { b0 = 0; b1 = 0; }
        mma16816(acc[ks % 3], a0, a1, a2, a3, b0, b1);
    }
    if (t < 2) {
        float2 v0 = make_float2(acc[0][0] + acc[1][0] + acc[2][0], acc[0][1] + acc[1][1] + acc[2][1]);
        float2 v1 = make_float2(acc[0][2] + acc[1][2] + acc[2][2], acc[0][3] + acc[1][3] + acc[2][3]);
        *reinterpret_cast<float2*>(red + (kg * 32 + 16 * mt + g) * 4 + 2 * t) = v0;
        *reinterpret_cast<float2*>(red + (kg * 32 + 16 * mt + g + 8) * 4 + 2 * t) = v1;
    }
}

DEVINL void row_gemv16(uint32_t wbase, uint32_t v_s, float (&acc)[5][4], int warp, int lane) {
    const int g = lane >> 2, t = lane & 3;
    const int j = lane >> 3, r = lane & 7;
    const int nb = 2 * warp + (j & 1);
    const int line0 = ((j >> 1) * 8 + r) * 9 + (nb >> 3);
    const uint32_t baddr = v_s + ((g & 3) * APITCH + 2 * t) * 2;
    uint32_t b0 = lds32(baddr), b1 = lds32(baddr + 16);
    if (g >= 4) { b0 = 0; b1 = 0; }
#pragma unroll
    for (int i = 0; i < 5; ++i) {
        if (i < 4 || warp < 4) {
            const int line = line0 + 2 * i;
            uint32_t a0, a1, a2, a3;
            ldsm4t(wbase + line * 128 + (((nb ^ line) & 7) << 4), a0, a1, a2, a3);
            mma16816(acc[i], a0, a1, a2, a3, b0, b1);
        }
    }
}

struct Maps { CUtensorMap wq, k, v, w1, w2, wo; };

__global__ void __launch_bounds__(NTHREADS, 1)
fused_kernel(const __grid_constant__ Maps mp, const __nv_bfloat16* __restrict__ x,
             const __nv_bfloat16* __restrict__ b1, __nv_bfloat16* __restrict__ out) {
    extern __shared__ __align__(1024) unsigned char smem[];
    const uint32_t sb = smem_u32(smem);
    const int tid = threadIdx.x, warp = tid >> 5, lane = tid & 31;
    const int cta = blockIdx.x;
    const bool is_att = cta < NATT;
    const int kvh = cta >> 3, rk = cta & 7;
    const uint32_t bars = sb + OFF_BAR;
    auto BAR = [&](int i) { return bars + 8u * i; };
    const int funit = is_att ? cta : NATT + (cta - NATT) * 4;
    const int kvline = (((rk >> 1) * HKV + kvh) * SK + (SK - WIN) + (rk & 1) * (WIN / 2)) * 2;

    if (tid == 256) {
        prefetch_tmap(&mp.wq);
        prefetch_tmap(&mp.k);
        mbar_init(BAR(0), 1); mbar_init(BAR(22), 1); mbar_init(BAR(23), 1);
        asm volatile("fence.mbarrier_init.release.cluster;" ::: "memory");
        TL(32);
        if (is_att) {
#pragma unroll
            for (int h = 0; h < 2; ++h) {
                mbar_expect_tx(BAR(22 + h), HALF_BYTES);
                tma_2d_keep(sb + OFF_WA + h * HALF_BYTES, &mp.wq, cta * 32, h * 288, BAR(22 + h));
                tma_2d_keep(sb + OFF_WA + h * HALF_BYTES + HALF_BYTES / 2, &mp.wq, cta * 32, h * 288 + 144, BAR(22 + h));
            }
            mbar_expect_tx(BAR(0), SLOT_BYTES);
            tma_2d(sb, &mp.k, 0, kvline, BAR(0));
        }
        TL(33);
#pragma unroll
        for (int i = 1; i < NBAR; ++i)
            if (i != 22 && i != 23) mbar_init(BAR(i), 1);
        asm volatile("fence.mbarrier_init.release.cluster;" ::: "memory");
        prefetch_tmap(&mp.w1);
        prefetch_tmap(&mp.v);
        prefetch_tmap(&mp.w2);
        prefetch_tmap(&mp.wo);
        reinterpret_cast<volatile int*>(smem + OFF_BAR + 336)[0] = 0;
        reinterpret_cast<volatile int*>(smem + OFF_BAR + 336)[1] = 0;
    }
    volatile int* prog_s = reinterpret_cast<volatile int*>(smem + OFF_BAR + 336);
    if (tid == 0) TL(0);
    if (warp == 8) {
        __syncwarp();
        asm volatile("bar.arrive 0, 352;" ::: "memory");
        if (lane != 0) return;
        if (is_att) {
            int kv = 1, wi = 0;
            int phase = 0;
            uint32_t inflight = (1u << 22) | (1u << 23) | 1u;
#pragma unroll 1
            for (int n = 3; n < 24; ++n) {
                for (unsigned it = 0; it < SPIN_LIMIT; ++it) {
                    int pace = phase == 0 ? PACE_A : (kv < 16 ? PACE : (phase == 1 ? PACE_END : PACE_FIN));
                    const int lag = *prog_s - (n - 3) * NATT;
                    pace += lag >= 2 * BAL_UP ? 2 : (lag >= BAL_UP ? 1 : (lag <= -BAL_DN ? -1 : 0));
                    pace = max(pace, 2);
                    if (__popc(inflight) < pace) break;
                    for (uint32_t rem = inflight; rem; rem &= rem - 1) {
                        const int id = __ffs(rem) - 1;
                        if (mbar_test(BAR(BAR_FULL + id), 0)) inflight &= ~(1u << id);
                    }
                    if (phase < 2 && mbar_test(BAR(phase == 0 ? BAR_Q : BAR_O), 0)) ++phase;
                }
                bool take_kv = kv < 16;
                if (take_kv && kv >= NSLOT && !mbar_test(BAR(BAR_EMPTY + kv - NSLOT), 0)) {
                    if (wi < NFILL) take_kv = false;
                    else mbar_wait(BAR(BAR_EMPTY + kv - NSLOT), 0);
                }
                const int i = take_kv ? kv++ : 16 + wi++;
                TL(32 + n);
                inflight |= 1u << i;
                const uint32_t fb = BAR(BAR_FULL + i);
                const int h = i & 1;
                if (i == 20) mbar_wait(BAR(BAR_WQFREE), 0);
                mbar_expect_tx(fb, i < 16 ? SLOT_BYTES : HALF_BYTES);
                if (i < 16) {
                    tma_2d(sb + (i % NSLOT) * SLOT_BYTES, i < 8 ? &mp.k : &mp.v, 0, kvline + (i & 7) * 128, fb);
                } else if (i < 18) {
                    tma_2d_keep(sb + OFF_WB + h * HALF_BYTES, &mp.w1, cta * 32, h * 288, fb);
                    tma_2d_keep(sb + OFF_WB + h * HALF_BYTES + HALF_BYTES / 2, &mp.w1, cta * 32, h * 288 + 144, fb);
                } else {
                    tma_2d(sb + (i < 20 ? OFF_WC : OFF_WA) + h * HALF_BYTES, i < 20 ? &mp.w2 : &mp.wo, 0,
                           cta * 288 + h * 144, fb);
                }
                red_add64(&g_prog, 1);
            }
            prog_s[1] = 1;
            TL(15);
        } else {
#pragma unroll 1
            for (int i = 0; i < 16; ++i) {
                if (i >= PACE) mbar_wait(BAR(BAR_FULL + i - PACE), 0);
                const uint32_t fb = BAR(BAR_FULL + i);
                const int u = (i >> 1) & 3, h = i & 1;
                if (i >= 8 && u > 0 && h == 0) mbar_wait(BAR(BAR_EMPTY + u - 1), 0);
                mbar_expect_tx(fb, HALF_BYTES);
                if (i < 8) {
                    tma_2d_keep(sb + u * REG_BYTES + h * HALF_BYTES, &mp.w1, (funit + u) * 32, h * 288, fb);
                    tma_2d_keep(sb + u * REG_BYTES + h * HALF_BYTES + HALF_BYTES / 2, &mp.w1, (funit + u) * 32, h * 288 + 144, fb);
                } else {
                    tma_2d(sb + (u == 0 ? 4 : u - 1) * REG_BYTES + h * HALF_BYTES, &mp.w2, 0, (funit + u) * 288 + h * 144, fb);
                }
            }
        }
        return;
    }

    uint32_t xw[9];
    unsigned short xres = 0;
    unsigned long long done0 = 0;
    if (warp < 4) {
        const uint32_t* xp = reinterpret_cast<const uint32_t*>(x) + warp * (DM / 2);
#pragma unroll
        for (int j = 0; j < 9; ++j) xw[j] = __ldg(xp + lane + 32 * j);
    }
    if (cta >= RED0 && warp == 0) {
        const int jr = cta - RED0, pc = lane >> 2, e = lane & 3;
        const int n = 16 * (jr >> 1) + (jr & 1) * 4 + (pc >> 1) + 8 * (e >> 1);
        const int b = 2 * (pc & 1) + (e & 1);
        xres = __ldg(reinterpret_cast<const unsigned short*>(x) + b * DM + n);
    }
    uint32_t cnt_target = 0;
    volatile uint32_t* ep_s = reinterpret_cast<volatile uint32_t*>(smem + OFF_BAR + 304);
    if (warp == 9) {
        if (lane == 2) done0 = ld_rlx64(&g_done);
        if (is_att && lane < 2) cnt_target = ld_rlx(g_cnt + cta * 32 + lane);
    }
    asm volatile("bar.sync 0, 352;" ::: "memory");

    if (warp == 10) {
        if (is_att && lane == 0) {
            for (unsigned it = 0; it < SPIN_LIMIT && !prog_s[1]; ++it) {
                prog_s[0] = (int)(ld_rlx64(&g_prog) % (NATT * 21));
                __nanosleep(BAL_SLEEP);
            }
        }
        return;
    }

    if (warp == 9) {
        if (lane == 2) {
            done0 = done0 / NCTA + 1;
            ep_s[4] = (uint32_t)done0 & 3u;
            *reinterpret_cast<volatile unsigned long long*>(smem + OFF_BAR + 312) = done0 * NCTA;
        }
        if (lane < 2) { cnt_target = (cnt_target & ~7u) + 8u; ep_s[lane] = cnt_target; }
        __syncwarp();
        if (lane == 0) mbar_arrive(BAR(BAR_EP));
        const uint32_t ep = ep_s[4];
        bool xchg = is_att;
        if (xchg) {
            mbar_wait(BAR(BAR_WQFREE), 0);
            if (lane == 0) wait_count(g_cnt + cta * 32, cnt_target);
            __syncwarp();
            {
                const uint32_t* src = g_qbox + cta * 256 + lane * 8;
                uint4 v0, v1;
                for (unsigned it = 0; it < SPIN_LIMIT; ++it) {
                    v0 = ld_rlx4(src); v1 = ld_rlx4(src + 4);
                    if (all_set(v0, ep) && all_set(v1, ep)) break;
                }
                *reinterpret_cast<uint4*>(smem + OFF_Q + lane * 16) =
                    make_uint4(__byte_perm(v0.x, v0.y, 0x7632), __byte_perm(v0.z, v0.w, 0x7632),
                               __byte_perm(v1.x, v1.y, 0x7632), __byte_perm(v1.z, v1.w, 0x7632));
                __syncwarp();
                if (lane == 0) mbar_arrive(BAR(BAR_Q));
            }
            mbar_wait(BAR(BAR_FULL + 15), 0);
            if (lane == 1) wait_count(g_cnt + cta * 32 + 1, cnt_target);
            __syncwarp();
            uint32_t* s0 = g_obox + cta * 8 * 64;
            uint32_t* se = s0 + (lane >> 3) * 64 + 32 + (lane & 7);
            uint32_t v[8], e0 = 0, e1 = 0;
            for (unsigned it = 0; it < SPIN_LIMIT; ++it) {
#pragma unroll
                for (int i = 0; i < 8; ++i) v[i] = ld_rlx(s0 + i * 64 + lane);
                e0 = ld_rlx(se); e1 = ld_rlx(se + 4 * 64);
                bool ok = tag_ok(e0, ep) && tag_ok(e1, ep);
#pragma unroll
                for (int i = 0; i < 8; ++i) ok = ok && tag_ok(v[i], ep);
                if (__all_sync(0xffffffffu, ok)) break;
            }
#pragma unroll
            for (int b = 0; b < 4; ++b) {
                const uint32_t e = b < 2 ? e0 : e1;
                const int sl = (b & 1) * 16;
                const float m0 = __uint_as_float(__shfl_sync(0xffffffffu, e, sl)), l0 = __uint_as_float(__shfl_sync(0xffffffffu, e, sl + 1));
                const float m1 = __uint_as_float(__shfl_sync(0xffffffffu, e, sl + 8)), l1 = __uint_as_float(__shfl_sync(0xffffffffu, e, sl + 9));
                const float M = fmaxf(m0, m1);
                const float f0 = exp2f(m0 - M), f1 = exp2f(m1 - M);
                const float o = __fdividef(__uint_as_float(v[2 * b]) * f0 + __uint_as_float(v[2 * b + 1]) * f1, l0 * f0 + l1 * f1);
                reinterpret_cast<__nv_bfloat16*>(smem + OFF_O)[b * APITCH + lane] = __float2bfloat16_rn(o);
            }
            __syncwarp();
            if (lane == 0) mbar_arrive(BAR(BAR_O));
            if (lane == 0) TL(14);
        }
        return;
    }

    const int g = lane >> 2, t = lane & 3;
    float* red = reinterpret_cast<float*>(smem + OFF_RED);

    if (warp < 4) {
        float s = 0.f;
#pragma unroll
        for (int j = 0; j < 9; ++j) s += bf_lo(xw[j]) + bf_hi(xw[j]);
#pragma unroll
        for (int o = 16; o; o >>= 1) s += __shfl_xor_sync(0xffffffffu, s, o);
        const float mean = s * (1.f / DM);
        float v = 0.f;
#pragma unroll
        for (int j = 0; j < 9; ++j) {
            float a = bf_lo(xw[j]) - mean, c = bf_hi(xw[j]) - mean;
            v += a * a + c * c;
        }
#pragma unroll
        for (int o = 16; o; o >>= 1) v += __shfl_xor_sync(0xffffffffu, v, o);
        const float mb = bf16r(mean);
        const float rden = 1.f / bf16r(sqrtf(bf16r(bf16r(v * (1.f / DM)) + 1e-5f)));
        uint32_t* xs = reinterpret_cast<uint32_t*>(smem + OFF_XN + warp * XPITCH * 2);
#pragma unroll
        for (int j = 0; j < 9; ++j)
            xs[lane + 32 * j] = pack_bf16(bf16r(bf_lo(xw[j]) - mb) * rden, bf16r(bf_hi(xw[j]) - mb) * rden);
    }
    cbar();
    mbar_wait(BAR(BAR_EP), 0);
    const uint32_t ep = ep_s[4];

    float acc[5][4] = {};

    if (is_att) {
        mbar_wait(BAR(BAR_FULL + 22 + (warp >> 2)), 0);
        if (tid == 0) TL(1);
        col_gemv(sb + OFF_WA, sb + OFF_XN, red, warp, lane);
        cbar();
        if (tid < 128) {
            const int b = warp;
            const float v = red[lane * 4 + b] + red[(32 + lane) * 4 + b] + red[(64 + lane) * 4 + b] + red[(96 + lane) * 4 + b];
            const uint32_t w = encf(bf16r(v), ep);
            uint32_t* dst = g_qbox + (kvh * 8 + 2 * b) * 256 + rk * 32 + lane;
            st_rlx(dst, w);
            st_rlx(dst + 256, w);
            if (lane < 2) red_add32(g_cnt + (kvh * 8 + 2 * b + lane) * 32, 1);
        }
        if (tid == 0) { mbar_arrive(BAR(BAR_WQFREE)); TL(2); }
        mbar_wait(BAR(BAR_Q), 0);
        if (tid == 0) TL(3);

        uint4 qa[4];
#pragma unroll
        for (int j = 0; j < 4; ++j) {
            qa[j] = lds128(sb + OFF_Q + (g & 1) * 256 + j * 64 + t * 16);
            if (g >= 2) qa[j] = make_uint4(0, 0, 0, 0);
        }
        float s[8][2];
        {
            const int f = (g >> 1) ^ (2 * (g & 1));
            const uint32_t kb = sb + (warp % NSLOT) * SLOT_BYTES + (4 * (g & 1) + f) * 256;
            uint32_t ko[4];
#pragma unroll
            for (int j = 0; j < 4; ++j) ko[j] = kb + (j >> 1) * 128 + (((4 * (j & 1) + t) ^ (2 * f + (j >> 1))) << 4);
            mbar_wait(BAR(BAR_FULL + warp), 0);
#pragma unroll
            for (int T = 0; T < 8; ++T) {
                float c[4] = {0.f, 0.f, 0.f, 0.f};
#pragma unroll
                for (int j = 0; j < 4; ++j) {
                    const uint4 kv = lds128(ko[j] + T * 2048);
                    mma16816(c, qa[j].x, 0u, qa[j].y, 0u, kv.x, kv.y);
                    mma16816(c, qa[j].z, 0u, qa[j].w, 0u, kv.z, kv.w);
                }
                s[T][0] = c[0];
                s[T][1] = c[1];
            }
            __syncwarp();
            if (lane == 0) mbar_arrive(BAR(BAR_EMPTY + warp));
        }
        if (lane == 0 && (warp == 0 || warp == 7)) TL(warp == 0 ? 4 : 5);
        const float cs = 0.08838834764831845f * 1.4426950408889634f;
        float m = s[0][0];
#pragma unroll
        for (int T = 0; T < 8; ++T) m = fmaxf(m, fmaxf(s[T][0], s[T][1]));
        m = fmaxf(m, __shfl_xor_sync(0xffffffffu, m, 1));
        m = fmaxf(m, __shfl_xor_sync(0xffffffffu, m, 2));
        const float mc = m * cs;
        float l = 0.f;
        uint32_t pb[8];
#pragma unroll
        for (int T = 0; T < 8; ++T) {
            const float p0 = exp2f(fmaf(s[T][0], cs, -mc)), p1 = exp2f(fmaf(s[T][1], cs, -mc));
            l += p0 + p1;
            pb[T] = pack_bf16(p0, p1);
        }
        l += __shfl_xor_sync(0xffffffffu, l, 1);
        l += __shfl_xor_sync(0xffffffffu, l, 2);
        float2* ml = reinterpret_cast<float2*>(smem + OFF_ML);
        if (g < 2 && t == 0) ml[warp * 2 + g] = make_float2(mc, l);

        {
            const int c = 8 + warp;
            const uint32_t vb = sb + (c % NSLOT) * SLOT_BYTES;
            uint32_t vo[2][2];
#pragma unroll
            for (int e = 0; e < 2; ++e)
#pragma unroll
                for (int hf = 0; hf < 2; ++hf) {
                    const int f = t ^ (2 * e);
                    vo[e][hf] = vb + (4 * e + f) * 256 + hf * 128 + ((g ^ (2 * f + hf)) << 4);
                }
            mbar_wait(BAR(BAR_FULL + c), 0);
            float o[2][4][4] = {};
#pragma unroll
            for (int ks = 0; ks < 4; ++ks) {
#pragma unroll
                for (int hf = 0; hf < 2; ++hf) {
                    const uint4 R0 = lds128(vo[0][hf] + ks * 4096), R1 = lds128(vo[1][hf] + ks * 4096);
                    const uint4 R2 = lds128(vo[0][hf] + ks * 4096 + 2048), R3 = lds128(vo[1][hf] + ks * 4096 + 2048);
                    const uint32_t r0[4] = {R0.x, R0.y, R0.z, R0.w}, r1[4] = {R1.x, R1.y, R1.z, R1.w};
                    const uint32_t r2[4] = {R2.x, R2.y, R2.z, R2.w}, r3[4] = {R3.x, R3.y, R3.z, R3.w};
#pragma unroll
                    for (int j = 0; j < 4; ++j)
                        mma16816(o[hf][j], __byte_perm(r0[j], r1[j], 0x5410), __byte_perm(r0[j], r1[j], 0x7632),
                                 __byte_perm(r2[j], r3[j], 0x5410), __byte_perm(r2[j], r3[j], 0x7632),
                                 pb[2 * ks], pb[2 * ks + 1]);
                }
            }
            __syncwarp();
            if (lane == 0 && c + NSLOT < 16) mbar_arrive(BAR(BAR_EMPTY + c));
            if (t == 0) {
                float* op = reinterpret_cast<float*>(smem + OFF_OP) + warp * 256 + 8 * g;
#pragma unroll
                for (int hf = 0; hf < 2; ++hf)
#pragma unroll
                    for (int jp = 0; jp < 2; ++jp) {
                        *reinterpret_cast<float4*>(op + 64 * hf + 4 * jp) =
                            make_float4(o[hf][2 * jp][0], o[hf][2 * jp][2], o[hf][2 * jp + 1][0], o[hf][2 * jp + 1][2]);
                        *reinterpret_cast<float4*>(op + 128 + 64 * hf + 4 * jp) =
                            make_float4(o[hf][2 * jp][1], o[hf][2 * jp][3], o[hf][2 * jp + 1][1], o[hf][2 * jp + 1][3]);
                    }
            }
        }
        cbar();
        if (tid == 0) TL(6);
        {
            const int head = tid >> 7;
            float M = ml[head].x;
#pragma unroll
            for (int w = 1; w < 8; ++w) M = fmaxf(M, ml[w * 2 + head].x);
            const float* op = reinterpret_cast<const float*>(smem + OFF_OP) + tid;
            float o = 0.f, L = 0.f;
#pragma unroll
            for (int w = 0; w < 8; ++w) {
                const float2 e = ml[w * 2 + head];
                const float f = exp2f(e.x - M);
                o = fmaf(f, op[w * 256], o);
                L = fmaf(f, e.y, L);
            }
            uint32_t* dst = g_obox + ((kvh * 8 + warp) * 8 + rk) * 64;
            st_rlx(dst + lane, encf(o, ep));
            if (lane < 8) st_rlx(dst + 32 + lane, encf((lane & 1) ? L : M, ep));
            if (lane == 0) red_add32(g_cnt + (kvh * 8 + warp) * 32 + 1, 1);
        }
        if (tid == 0) TL(7);
    }

    const int nu = is_att ? 1 : 4;
#pragma unroll 1
    for (int u = 0; u < nu; ++u) {
        float bias = 0.f;
        if (tid < 128) bias = __bfloat162float(b1[(funit + u) * 32 + (tid >> 2)]);
        mbar_wait(BAR(BAR_FULL + (is_att ? 16 : 2 * u) + (warp >> 2)), 0);
        if (tid == 0) TL(8);
        col_gemv(sb + (is_att ? OFF_WB : u * REG_BYTES), sb + OFF_XN, red, warp, lane);
        cbar();
        if (tid == 0 && u < nu - 1) mbar_arrive(BAR(BAR_EMPTY + u));
        if (tid < 128) {
            float h = red[tid] + red[128 + tid] + red[256 + tid] + red[384 + tid];
            h = bf16r(bf16r(h) + bias);
            reinterpret_cast<__nv_bfloat16*>(smem + OFF_ACT + u * 320)[(tid & 3) * APITCH + (tid >> 2)] =
                __float2bfloat16_rn(mish(h));
        }
        cbar();
    }
    if (tid == 0) TL(9);

    const int nr = is_att ? 4 : 8;
#pragma unroll 1
    for (int i = 0; i < nr; ++i) {
        const int u = i >> 1, h = i & 1;
        if (is_att && i == 2) mbar_wait(BAR(BAR_O), 0);
        mbar_wait(BAR(BAR_FULL + (is_att ? 18 : 8) + i), 0);
        if (tid == 0 && i == nr - 1) red_add64(&g_done, 1);
        if (tid == 0 && (i == 0 || i == nr - 1)) TL(i == 0 ? 10 : 11);
        const uint32_t wbase = is_att ? (u ? OFF_WA : OFF_WC) : (u == 0 ? 4 : u - 1) * REG_BYTES;
        const uint32_t vbase = is_att ? (u ? OFF_O : OFF_ACT) : OFF_ACT + u * 320;
        row_gemv16(sb + wbase + h * HALF_BYTES, sb + vbase + h * 32, acc, warp, lane);
    }

    if (t < 2) {
#pragma unroll
        for (int i = 0; i < 5; ++i) {
            if (i < 4 || warp < 4) {
                const int jr = 2 * (warp + 8 * i) + (g >> 2);
                uint32_t* dst = g_part + ((size_t)(jr * NCTA + cta) * 32 + ((g & 3) * 2 + t) * 4);
                st_rlx4(dst, make_uint4(encf(acc[i][0], ep), encf(acc[i][1], ep), encf(acc[i][2], ep), encf(acc[i][3], ep)));
            }
        }
    }
    if (tid == 0) TL(12);

    if (cta >= RED0) {
        const int jr = cta - RED0;
        const int p0 = (lane >> 3) + 4 * warp;
        uint32_t* src = g_part + ((size_t)(jr * NCTA + p0) * 32 + (lane & 7) * 4);
        const bool has4 = p0 + 128 < NCTA;
        uint4 v[5];
        unsigned pend = has4 ? 31u : 15u;
        v[4] = make_uint4(0, 0, 0, 0);
        if (lane == 0) {
            const unsigned long long tgt = *reinterpret_cast<volatile unsigned long long*>(smem + OFF_BAR + 312);
            for (unsigned it = 0; it < SPIN_LIMIT; ++it) {
                const unsigned long long d = ld_rlx64(&g_done);
                if (d >= tgt) break;
                if (d + 64 < tgt) __nanosleep(200);
            }
        }
        __syncwarp();
        for (unsigned it = 0; it < SPIN_LIMIT; ++it) {
#pragma unroll
            for (int i = 0; i < 5; ++i)
                if (pend & (1u << i)) v[i] = ld_rlx4(src + i * 32 * 32);
#pragma unroll
            for (int i = 0; i < 5; ++i)
                if ((pend & (1u << i)) && all_set(v[i], ep)) pend &= ~(1u << i);
            if (!pend) break;
        }
        float4 a = make_float4(0.f, 0.f, 0.f, 0.f);
#pragma unroll
        for (int i = 0; i < 5; ++i) {
            a.x += __uint_as_float(v[i].x); a.y += __uint_as_float(v[i].y);
            a.z += __uint_as_float(v[i].z); a.w += __uint_as_float(v[i].w);
        }
#pragma unroll
        for (int o = 8; o <= 16; o <<= 1) {
            a.x += __shfl_xor_sync(0xffffffffu, a.x, o); a.y += __shfl_xor_sync(0xffffffffu, a.y, o);
            a.z += __shfl_xor_sync(0xffffffffu, a.z, o); a.w += __shfl_xor_sync(0xffffffffu, a.w, o);
        }
        if (lane < 8) *reinterpret_cast<float4*>(red + warp * 32 + lane * 4) = a;
        cbar();
        if (tid < 32) {
            float r = __uint_as_float((uint32_t)xres << 16);
#pragma unroll
            for (int w = 0; w < 8; ++w) r += red[w * 32 + tid];
            const int pc = tid >> 2, e = tid & 3;
            const int n = 16 * (jr >> 1) + (jr & 1) * 4 + (pc >> 1) + 8 * (e >> 1);
            const int b = 2 * (pc & 1) + (e & 1);
            out[b * DM + n] = __float2bfloat16_rn(r);
        }
        if (tid == 0) TL(13);
    }
}

__device__ void fb_layernorm(const __nv_bfloat16* x, float* xn  ) {
    const int warp = threadIdx.x >> 5, lane = threadIdx.x & 31;
    if (warp < NB) {
        float s = 0.f;
        for (int i = lane; i < DM; i += 32) s += __bfloat162float(x[warp * DM + i]);
        for (int o = 16; o; o >>= 1) s += __shfl_xor_sync(0xffffffffu, s, o);
        const float mean = s / DM;
        float v = 0.f;
        for (int i = lane; i < DM; i += 32) { float d = __bfloat162float(x[warp * DM + i]) - mean; v += d * d; }
        for (int o = 16; o; o >>= 1) v += __shfl_xor_sync(0xffffffffu, v, o);
        const float mb = bf16r(mean);
        const float den = bf16r(sqrtf(bf16r(bf16r(v / DM) + 1e-5f)));
        for (int i = lane; i < DM; i += 32)
            xn[warp * DM + i] = bf16r(bf16r(__bfloat162float(x[warp * DM + i]) - mb) / den);
    }
    __syncthreads();
}

__global__ void fb_proj(const __nv_bfloat16* x, const __nv_bfloat16* wq, const __nv_bfloat16* w1,
                        const __nv_bfloat16* b1) {
    __shared__ float xn[NB * DM];
    fb_layernorm(x, xn);
    const int c = blockIdx.x * blockDim.x + threadIdx.x;
    if (c >= QD + FF) return;
    const bool isq = c < QD;
    const __nv_bfloat16* w = isq ? wq + c : w1 + (c - QD);
    const int pitch = isq ? QD : FF;
    float a[NB] = {};
    for (int k = 0; k < DM; ++k) {
        const float wv = __bfloat162float(w[(size_t)k * pitch]);
        for (int b = 0; b < NB; ++b) a[b] = fmaf(xn[b * DM + k], wv, a[b]);
    }
    for (int b = 0; b < NB; ++b) {
        if (isq) g_fb_q[b * QD + c] = __float2bfloat16_rn(a[b]);
        else {
            const float h = bf16r(bf16r(a[b]) + __bfloat162float(b1[c - QD]));
            g_fb_act[b * FF + c - QD] = __float2bfloat16_rn(mish(h));
        }
    }
}

__global__ void fb_attn(const __nv_bfloat16* kc, const __nv_bfloat16* vc) {
    __shared__ float q[DH], p[WIN], rd[128];
    const int b = blockIdx.x / HQ, h = blockIdx.x % HQ, tid = threadIdx.x;
    const size_t base = ((size_t)(b * HKV + h / 2) * SK + (SK - WIN)) * DH;
    q[tid] = __bfloat162float(g_fb_q[b * QD + h * DH + tid]);
    __syncthreads();
    float m = -INFINITY;
    for (int k = tid; k < WIN; k += 128) {
        float s = 0.f;
        for (int d = 0; d < DH; ++d) s = fmaf(q[d], __bfloat162float(kc[base + (size_t)k * DH + d]), s);
        s *= 0.08838834764831845f;
        p[k] = s;
        m = fmaxf(m, s);
    }
    rd[tid] = m;
    __syncthreads();
    for (int i = 0; i < 128; ++i) m = fmaxf(m, rd[i]);
    __syncthreads();
    float l = 0.f;
    for (int k = tid; k < WIN; k += 128) { p[k] = expf(p[k] - m); l += p[k]; }
    rd[tid] = l;
    __syncthreads();
    l = 0.f;
    for (int i = 0; i < 128; ++i) l += rd[i];
    float o = 0.f;
    for (int k = 0; k < WIN; ++k) o = fmaf(p[k], __bfloat162float(vc[base + (size_t)k * DH + tid]), o);
    g_fb_o[b * QD + h * DH + tid] = __float2bfloat16_rn(o / l);
}

__global__ void fb_out(const __nv_bfloat16* x, const __nv_bfloat16* wo, const __nv_bfloat16* w2,
                       __nv_bfloat16* out) {
    __shared__ float rd[8][NB][32];
    const int n = blockIdx.x * 32 + (threadIdx.x & 31), part = threadIdx.x >> 5;
    float a[NB] = {};
    for (int k = part; k < QD; k += 8) {
        const float wv = __bfloat162float(wo[(size_t)k * DM + n]);
        for (int b = 0; b < NB; ++b) a[b] = fmaf(__bfloat162float(g_fb_o[b * QD + k]), wv, a[b]);
    }
    for (int k = part; k < FF; k += 8) {
        const float wv = __bfloat162float(w2[(size_t)k * DM + n]);
        for (int b = 0; b < NB; ++b) a[b] = fmaf(__bfloat162float(g_fb_act[b * FF + k]), wv, a[b]);
    }
    for (int b = 0; b < NB; ++b) rd[part][b][threadIdx.x & 31] = a[b];
    __syncthreads();
    if (threadIdx.x < 128) {
        const int b = threadIdx.x >> 5, c = threadIdx.x & 31;
        float r = __bfloat162float(x[b * DM + blockIdx.x * 32 + c]);
        for (int i = 0; i < 8; ++i) r += rd[i][b][c];
        out[b * DM + blockIdx.x * 32 + c] = __float2bfloat16_rn(r);
    }
}

void launch_fallback(const __nv_bfloat16* x, const __nv_bfloat16* kc, const __nv_bfloat16* vc,
                     const __nv_bfloat16* wq, const __nv_bfloat16* wo, const __nv_bfloat16* w1,
                     const __nv_bfloat16* b1, const __nv_bfloat16* w2, __nv_bfloat16* out) {
    fb_proj<<<(QD + FF) / 128, 128>>>(x, wq, w1, b1);
    fb_attn<<<NB * HQ, 128>>>(kc, vc);
    fb_out<<<DM / 32, 256>>>(x, wo, w2, out);
}

typedef CUresult (*EncodeFn)(CUtensorMap*, CUtensorMapDataType, cuuint32_t, void*, const cuuint64_t*, const cuuint64_t*,
                             const cuuint32_t*, const cuuint32_t*, CUtensorMapInterleave, CUtensorMapSwizzle,
                             CUtensorMapL2promotion, CUtensorMapFloatOOBfill);

#define L2PROMO CU_TENSOR_MAP_L2_PROMOTION_L2_128B

#define L2PROMO2 CU_TENSOR_MAP_L2_PROMOTION_L2_128B
bool make_map(EncodeFn fn, CUtensorMap* m, const void* base, uint64_t cols, uint64_t rows, uint32_t box_cols,
              uint32_t box_rows, CUtensorMapSwizzle sw) {
    cuuint64_t dims[2] = {cols, rows};
    cuuint64_t strides[1] = {cols * 2};
    cuuint32_t box[2] = {box_cols, box_rows};
    cuuint32_t es[2] = {1, 1};
    return fn(m, CU_TENSOR_MAP_DATA_TYPE_BFLOAT16, 2, const_cast<void*>(base), dims, strides, box, es,
              CU_TENSOR_MAP_INTERLEAVE_NONE, sw, box_cols == 32 ? L2PROMO : L2PROMO2, CU_TENSOR_MAP_FLOAT_OOB_FILL_NONE) == CUDA_SUCCESS;
}

struct HostState {
    int ok;
    EncodeFn encode;
    const void* ptr[6];
    bool maps_ok;
    Maps maps;
};
HostState g_host = {-1, nullptr, {nullptr, nullptr, nullptr, nullptr, nullptr, nullptr}, false, {}};

bool fused_ready(const void* wq, const void* kc, const void* vc, const void* w1, const void* w2, const void* wo) {
    HostState& h = g_host;
    if (h.ok < 0) {
        int dev = 0, sms = 0, occ = 0, coop = 0;
        void* fn = nullptr;
        cudaDriverEntryPointQueryResult qr;
        h.ok = 0;
        if (cudaGetDevice(&dev) == cudaSuccess &&
            cudaDeviceGetAttribute(&sms, cudaDevAttrMultiProcessorCount, dev) == cudaSuccess &&
            cudaFuncSetAttribute(fused_kernel, cudaFuncAttributeMaxDynamicSharedMemorySize, SMEM_BYTES) == cudaSuccess &&
            cudaOccupancyMaxActiveBlocksPerMultiprocessor(&occ, fused_kernel, NTHREADS, SMEM_BYTES) == cudaSuccess &&
            sms * occ >= NCTA &&
            cudaDeviceGetAttribute(&coop, cudaDevAttrCooperativeLaunch, dev) == cudaSuccess && coop &&
            cudaGetDriverEntryPoint("cuTensorMapEncodeTiled", &fn, cudaEnableDefault, &qr) == cudaSuccess &&
            qr == cudaDriverEntryPointSuccess && fn) {
            h.encode = (EncodeFn)fn;
            h.ok = 1;
        }
        (void)cudaGetLastError();
    }
    if (h.ok != 1) return false;
    const void* p[6] = {wq, kc, vc, w1, w2, wo};
    bool same = true;
    for (int i = 0; i < 6; ++i) same = same && h.ptr[i] == p[i];
    if (!same) {
        for (int i = 0; i < 6; ++i) h.ptr[i] = p[i];
        const uint64_t kvlines = (uint64_t)NB * HKV * SK * DH / 64;
        h.maps_ok = make_map(h.encode, &h.maps.wq, wq, QD, DM, 32, 144, CU_TENSOR_MAP_SWIZZLE_64B) &&
                    make_map(h.encode, &h.maps.w1, w1, FF, DM, 32, 144, CU_TENSOR_MAP_SWIZZLE_64B) &&
                    make_map(h.encode, &h.maps.k, kc, 64, kvlines, 64, 128, CU_TENSOR_MAP_SWIZZLE_128B) &&
                    make_map(h.encode, &h.maps.v, vc, 64, kvlines, 64, 128, CU_TENSOR_MAP_SWIZZLE_128B) &&
                    make_map(h.encode, &h.maps.w2, w2, 64, (uint64_t)FF * DM / 64, 64, 144, CU_TENSOR_MAP_SWIZZLE_128B) &&
                    make_map(h.encode, &h.maps.wo, wo, 64, (uint64_t)QD * DM / 64, 64, 144, CU_TENSOR_MAP_SWIZZLE_128B);
    }
    return h.maps_ok;
}

}

extern "C" void kernel_launch(void* const* d_in, const int* in_sizes, int n_in, void* d_out, int out_size) {
    const __nv_bfloat16* x = (const __nv_bfloat16*)d_in[0];
    const __nv_bfloat16* kc = (const __nv_bfloat16*)d_in[1];
    const __nv_bfloat16* vc = (const __nv_bfloat16*)d_in[2];
    const __nv_bfloat16* wq = (const __nv_bfloat16*)d_in[3];
    const __nv_bfloat16* wo = (const __nv_bfloat16*)d_in[4];
    const __nv_bfloat16* w1 = (const __nv_bfloat16*)d_in[6];
    const __nv_bfloat16* b1 = (const __nv_bfloat16*)d_in[7];
    const __nv_bfloat16* w2 = (const __nv_bfloat16*)d_in[8];
    __nv_bfloat16* out = (__nv_bfloat16*)d_out;
    if (fused_ready(wq, kc, vc, w1, w2, wo)) {
        cudaLaunchConfig_t cfg = {};
        cfg.gridDim = dim3(NCTA);
        cfg.blockDim = dim3(NTHREADS);
        cfg.dynamicSmemBytes = SMEM_BYTES;
        cfg.stream = 0;
        cudaLaunchAttribute at[1];
        at[0].id = cudaLaunchAttributeCooperative;
        at[0].val.cooperative = 1;
        cfg.attrs = at;
        cfg.numAttrs = 1;
        cudaLaunchKernelEx(&cfg, fused_kernel, g_host.maps, x, b1, out);
    } else {
        launch_fallback(x, kc, vc, wq, wo, w1, b1, w2, out);
    }
}
```

```cpp
#include <cuda_runtime.h>
#include <cuda.h>
#include <cuda_bf16.h>
#include <stdint.h>

#define DEVINL __device__ __forceinline__

namespace {

constexpr int NB = 4;
constexpr int DM = 576;
constexpr int HQ = 32, HKV = 16, SK = 4096, DH = 128, WIN = 1024;
constexpr int FF = 4608;
constexpr int QD = HQ * DH;

constexpr int NATT = 128;
constexpr int NCTA = 132;
constexpr int NRED = 72;
constexpr int RED0 = NCTA - NRED;
constexpr int NTHREADS = 352;

constexpr int SLOT_BYTES = 16384;
constexpr int NSLOT = 6;
constexpr int REG_BYTES = 36864;
constexpr int HALF_BYTES = REG_BYTES / 2;
constexpr int OFF_WA = NSLOT * SLOT_BYTES;
constexpr int OFF_WB = OFF_WA + REG_BYTES;
constexpr int OFF_WC = OFF_WB + REG_BYTES;
constexpr int OFF_MISC = OFF_WC + REG_BYTES;
constexpr int XPITCH = 584;
constexpr int OFF_XN = OFF_MISC;
constexpr int OFF_RED = OFF_XN + NB * XPITCH * 2;
constexpr int OFF_Q = OFF_RED + 2048;
constexpr int OFF_ACT = OFF_Q + 512;
constexpr int OFF_O = OFF_ACT + 1280;
constexpr int OFF_ML = OFF_O + 320;
constexpr int OFF_BAR = OFF_ML + 128;
constexpr int OFF_OP = OFF_BAR + 352;
constexpr int SMEM_BYTES = OFF_OP + 8192;
static_assert(SMEM_BYTES <= 232448, "smem");
static_assert(OFF_RED % 16 == 0 && OFF_Q % 16 == 0 && OFF_OP % 16 == 0 && OFF_BAR % 8 == 0, "align");
static_assert(5 * REG_BYTES <= OFF_MISC, "ffn cta regions");
static_assert(OFF_WA % 1024 == 0 && HALF_BYTES % 1024 == 0, "swizzle atom alignment");

constexpr int APITCH = 40;

constexpr int BAR_FULL = 0;
constexpr int BAR_EMPTY = 24;
constexpr int BAR_WQFREE = 34, BAR_Q = 35, BAR_O = 36, BAR_EP = 37, NBAR = 38;

#define PACE_A 3
#define PACE 4
#define PACE_END 2
#define PACE_FIN 3
#define NFILL 2
#define BAL_UP 64
#define BAL_DN 96
#define BAL_SLEEP 100

constexpr unsigned SPIN_LIMIT = 1u << 20;

__device__ __align__(128) uint32_t g_qbox[NATT * 256];
__device__ __align__(128) uint32_t g_obox[NATT * 8 * 64];
__device__ __align__(128) uint32_t g_part[NRED * NCTA * 32];
__device__ __align__(128) uint32_t g_cnt[NATT * 32];
__device__ __align__(128) unsigned long long g_prog_line[16];
#define g_prog g_prog_line[0]
#define NREP 4
__device__ __align__(128) unsigned long long g_done[NREP * 16];

__device__ __nv_bfloat16 g_fb_q[NB * QD];
__device__ __nv_bfloat16 g_fb_act[NB * FF];
__device__ __nv_bfloat16 g_fb_o[NB * QD];

DEVINL uint32_t smem_u32(const void* p) { return (uint32_t)__cvta_generic_to_shared(p); }

DEVINL void mbar_init(uint32_t bar, uint32_t cnt) {
    asm volatile("mbarrier.init.shared::cta.b64 [%0], %1;" ::"r"(bar), "r"(cnt) : "memory");
}
DEVINL void mbar_expect_tx(uint32_t bar, uint32_t bytes) {
    asm volatile("mbarrier.arrive.expect_tx.shared::cta.b64 _, [%0], %1;" ::"r"(bar), "r"(bytes) : "memory");
}
DEVINL void mbar_arrive(uint32_t bar) {
    asm volatile("mbarrier.arrive.shared::cta.b64 _, [%0];" ::"r"(bar) : "memory");
}
DEVINL void mbar_wait(uint32_t bar, uint32_t parity) {
    uint32_t ok = 0;
    for (unsigned it = 0; it < SPIN_LIMIT; ++it) {
        asm volatile(
            "{\n\t.reg .pred p;\n\t"
            "mbarrier.try_wait.parity.shared::cta.b64 p, [%1], %2;\n\t"
            "selp.u32 %0, 1, 0, p;\n\t}"
            : "=r"(ok) : "r"(bar), "r"(parity) : "memory");
        if (ok) break;
    }
}
DEVINL bool mbar_test(uint32_t bar, uint32_t parity) {
    uint32_t ok;
    asm volatile(
        "{\n\t.reg .pred p;\n\t"
        "mbarrier.test_wait.parity.shared::cta.b64 p, [%1], %2;\n\t"
        "selp.u32 %0, 1, 0, p;\n\t}"
        : "=r"(ok) : "r"(bar), "r"(parity) : "memory");
    return ok != 0;
}
DEVINL void tma_2d(uint32_t dst, const CUtensorMap* map, int c0, int c1, uint32_t bar) {
    asm volatile(
        "cp.async.bulk.tensor.2d.shared::cluster.global.mbarrier::complete_tx::bytes.L2::cache_hint [%0], [%1, {%2, %3}], [%4], %5;"
        ::"r"(dst), "l"(map), "r"(c0), "r"(c1), "r"(bar), "l"(0x12F0000000000000ull) : "memory");
}
DEVINL void tma_2d_keep(uint32_t dst, const CUtensorMap* map, int c0, int c1, uint32_t bar) {
    asm volatile(
        "cp.async.bulk.tensor.2d.shared::cluster.global.mbarrier::complete_tx::bytes [%0], [%1, {%2, %3}], [%4];"
        ::"r"(dst), "l"(map), "r"(c0), "r"(c1), "r"(bar) : "memory");
}
DEVINL void prefetch_tmap(const CUtensorMap* map) {
    asm volatile("prefetch.tensormap [%0];" ::"l"(map) : "memory");
}
DEVINL void cbar() { asm volatile("bar.sync 1, 256;" ::: "memory"); }

DEVINL void ldsm4t(uint32_t addr, uint32_t& r0, uint32_t& r1, uint32_t& r2, uint32_t& r3) {
    asm volatile("ldmatrix.sync.aligned.m8n8.x4.trans.shared.b16 {%0,%1,%2,%3}, [%4];"
                 : "=r"(r0), "=r"(r1), "=r"(r2), "=r"(r3) : "r"(addr) : "memory");
}
DEVINL uint4 lds128(uint32_t addr) {
    uint4 v;
    asm volatile("ld.shared.v4.u32 {%0,%1,%2,%3}, [%4];" : "=r"(v.x), "=r"(v.y), "=r"(v.z), "=r"(v.w) : "r"(addr) : "memory");
    return v;
}
DEVINL uint32_t lds32(uint32_t addr) {
    uint32_t v;
    asm volatile("ld.shared.u32 %0, [%1];" : "=r"(v) : "r"(addr) : "memory");
    return v;
}
DEVINL void mma16816(float* c, uint32_t a0, uint32_t a1, uint32_t a2, uint32_t a3, uint32_t b0, uint32_t b1) {
    asm volatile(
        "mma.sync.aligned.m16n8k16.row.col.f32.bf16.bf16.f32 {%0,%1,%2,%3}, {%4,%5,%6,%7}, {%8,%9}, {%0,%1,%2,%3};"
        : "+f"(c[0]), "+f"(c[1]), "+f"(c[2]), "+f"(c[3])
        : "r"(a0), "r"(a1), "r"(a2), "r"(a3), "r"(b0), "r"(b1));
}
DEVINL uint32_t pack_bf16(float lo, float hi) {
    uint32_t r;
    asm("cvt.rn.bf16x2.f32 %0, %1, %2;" : "=r"(r) : "f"(hi), "f"(lo));
    return r;
}
DEVINL float bf16r(float x) { return __bfloat162float(__float2bfloat16_rn(x)); }
DEVINL float bf_lo(uint32_t w) { return __uint_as_float(w << 16); }
DEVINL float bf_hi(uint32_t w) { return __uint_as_float(w & 0xffff0000u); }

DEVINL uint32_t encf(float f, uint32_t ep) { return (__float_as_uint(f) & ~3u) | ep; }
DEVINL bool tag_ok(uint32_t w, uint32_t ep) { return (w & 3u) == ep; }
DEVINL float decf(uint32_t w) { return __uint_as_float(w & ~3u); }
DEVINL void st_rlx(uint32_t* p, uint32_t v) {
    asm volatile("st.relaxed.gpu.global.u32 [%0], %1;" ::"l"(p), "r"(v) : "memory");
}
DEVINL void st_rlx4(uint32_t* p, uint4 v) {
    asm volatile("st.relaxed.gpu.global.v4.u32 [%0], {%1,%2,%3,%4};" ::"l"(p), "r"(v.x), "r"(v.y), "r"(v.z), "r"(v.w) : "memory");
}
DEVINL uint32_t ld_rlx(const uint32_t* p) {
    uint32_t v;
    asm volatile("ld.relaxed.gpu.global.u32 %0, [%1];" : "=r"(v) : "l"(p) : "memory");
    return v;
}
DEVINL uint4 ld_rlx4(const uint32_t* p) {
    uint4 v;
    asm volatile("ld.relaxed.gpu.global.v4.u32 {%0,%1,%2,%3}, [%4];" : "=r"(v.x), "=r"(v.y), "=r"(v.z), "=r"(v.w) : "l"(p) : "memory");
    return v;
}
DEVINL unsigned long long ld_rlx64(const unsigned long long* p) {
    unsigned long long v;
    asm volatile("ld.relaxed.gpu.global.u64 %0, [%1];" : "=l"(v) : "l"(p) : "memory");
    return v;
}
DEVINL void red_add64(unsigned long long* p, unsigned long long v) {
    asm volatile("red.relaxed.gpu.global.add.u64 [%0], %1;" ::"l"(p), "l"(v) : "memory");
}
DEVINL void red_add32(uint32_t* p, uint32_t v) {
    asm volatile("red.relaxed.gpu.global.add.u32 [%0], %1;" ::"l"(p), "r"(v) : "memory");
}
DEVINL void wait_count(const uint32_t* p, uint32_t target) {
    for (unsigned it = 0; it < SPIN_LIMIT; ++it)
        if ((int)(ld_rlx(p) - target) >= 0) break;
}
DEVINL bool all_set(uint4 v, uint32_t ep) { return (((v.x ^ ep) | (v.y ^ ep) | (v.z ^ ep) | (v.w ^ ep)) & 3u) == 0; }

DEVINL float mish(float h) {
    float sp = log1pf(expf(-fabsf(h))) + fmaxf(h, 0.f);
    return h * tanhf(sp);
}

DEVINL void col_gemv(uint32_t wbase, uint32_t xn_s, float* red, int warp, int lane) {
    const int mt = warp & 1, kg = warp >> 1;
    const int g = lane >> 2, t = lane & 3;
    const int j = lane >> 3, r = lane & 7;
    const int chunk = 2 * mt + (j & 1);
    const uint32_t aaddr = wbase + (kg * 144 + (j >> 1) * 8 + r) * 64 + ((chunk ^ ((r >> 1) & 3)) << 4);
    const uint32_t baddr = xn_s + ((g & 3) * XPITCH + kg * 144 + 2 * t) * 2;
    float acc[3][4] = {};
#pragma unroll
    for (int ks = 0; ks < 9; ++ks) {
        uint32_t a0, a1, a2, a3;
        ldsm4t(aaddr + ks * 1024, a0, a1, a2, a3);
        uint32_t b0 = lds32(baddr + ks * 32), b1 = lds32(baddr + ks * 32 + 16);
        if (g >= 4) { b0 = 0; b1 = 0; }
        mma16816(acc[ks % 3], a0, a1, a2, a3, b0, b1);
    }
    if (t < 2) {
        float2 v0 = make_float2(acc[0][0] + acc[1][0] + acc[2][0], acc[0][1] + acc[1][1] + acc[2][1]);
        float2 v1 = make_float2(acc[0][2] + acc[1][2] + acc[2][2], acc[0][3] + acc[1][3] + acc[2][3]);
        *reinterpret_cast<float2*>(red + (kg * 32 + 16 * mt + g) * 4 + 2 * t) = v0;
        *reinterpret_cast<float2*>(red + (kg * 32 + 16 * mt + g + 8) * 4 + 2 * t) = v1;
    }
}

DEVINL void row_gemv16(uint32_t wbase, uint32_t v_s, float (&acc)[5][4], int warp, int lane) {
    const int g = lane >> 2, t = lane & 3;
    const int j = lane >> 3, r = lane & 7;
    const int nb = 2 * warp + (j & 1);
    const int line0 = ((j >> 1) * 8 + r) * 9 + (nb >> 3);
    const uint32_t baddr = v_s + ((g & 3) * APITCH + 2 * t) * 2;
    uint32_t b0 = lds32(baddr), b1 = lds32(baddr + 16);
    if (g >= 4) { b0 = 0; b1 = 0; }
#pragma unroll
    for (int i = 0; i < 5; ++i) {
        if (i < 4 || warp < 4) {
            const int line = line0 + 2 * i;
            uint32_t a0, a1, a2, a3;
            ldsm4t(wbase + line * 128 + (((nb ^ line) & 7) << 4), a0, a1, a2, a3);
            mma16816(acc[i], a0, a1, a2, a3, b0, b1);
        }
    }
}

struct Maps { CUtensorMap wq, k, v, w1, w2, wo; };

__global__ void __launch_bounds__(NTHREADS, 1)
fused_kernel(const __grid_constant__ Maps mp, const __nv_bfloat16* __restrict__ x,
             const __nv_bfloat16* __restrict__ b1, __nv_bfloat16* __restrict__ out) {
    extern __shared__ __align__(1024) unsigned char smem[];
    const uint32_t sb = smem_u32(smem);
    const int tid = threadIdx.x, warp = tid >> 5, lane = tid & 31;
    const int cta = blockIdx.x;
    const bool is_att = cta < NATT;
    const int kvh = cta >> 3, rk = cta & 7;
    const uint32_t bars = sb + OFF_BAR;
    auto BAR = [&](int i) { return bars + 8u * i; };
    const int funit = is_att ? cta : NATT + (cta - NATT) * 4;
    const int kvline = (((rk >> 1) * HKV + kvh) * SK + (SK - WIN) + (rk & 1) * (WIN / 2)) * 2;

    if (tid == 256) {
        prefetch_tmap(&mp.wq);
        prefetch_tmap(&mp.k);
        mbar_init(BAR(0), 1); mbar_init(BAR(22), 1); mbar_init(BAR(23), 1);
        asm volatile("fence.mbarrier_init.release.cluster;" ::: "memory");
        if (is_att) {
#pragma unroll
            for (int h = 0; h < 2; ++h) {
                mbar_expect_tx(BAR(22 + h), HALF_BYTES);
                tma_2d_keep(sb + OFF_WA + h * HALF_BYTES, &mp.wq, cta * 32, h * 288, BAR(22 + h));
                tma_2d_keep(sb + OFF_WA + h * HALF_BYTES + HALF_BYTES / 2, &mp.wq, cta * 32, h * 288 + 144, BAR(22 + h));
            }
            mbar_expect_tx(BAR(0), SLOT_BYTES);
            tma_2d(sb, &mp.k, 0, kvline, BAR(0));
        }
#pragma unroll
        for (int i = 1; i < NBAR; ++i)
            if (i != 22 && i != 23) mbar_init(BAR(i), 1);
        asm volatile("fence.mbarrier_init.release.cluster;" ::: "memory");
        prefetch_tmap(&mp.w1);
        prefetch_tmap(&mp.v);
        prefetch_tmap(&mp.w2);
        prefetch_tmap(&mp.wo);
        reinterpret_cast<volatile int*>(smem + OFF_BAR + 336)[0] = 0;
        reinterpret_cast<volatile int*>(smem + OFF_BAR + 336)[1] = 0;
    }
    volatile int* prog_s = reinterpret_cast<volatile int*>(smem + OFF_BAR + 336);
    if (warp == 8) {
        __syncwarp();
        asm volatile("bar.arrive 0, 352;" ::: "memory");
        if (lane != 0) return;
        if (is_att) {
            int kv = 1, wi = 0;
            int phase = 0;
            uint32_t inflight = (1u << 22) | (1u << 23) | 1u;
#pragma unroll 1
            for (int n = 3; n < 24; ++n) {
                for (unsigned it = 0; it < SPIN_LIMIT; ++it) {
                    int pace = phase == 0 ? PACE_A : (kv < 16 ? PACE : (phase == 1 ? PACE_END : PACE_FIN));
                    const int lag = *prog_s - (n - 3) * NATT;
                    pace += lag >= 2 * BAL_UP ? 2 : (lag >= BAL_UP ? 1 : (lag <= -BAL_DN ? -1 : 0));
                    pace = max(pace, 2);
                    if (__popc(inflight) < pace) break;
                    for (uint32_t rem = inflight; rem; rem &= rem - 1) {
                        const int id = __ffs(rem) - 1;
                        if (mbar_test(BAR(BAR_FULL + id), 0)) inflight &= ~(1u << id);
                    }
                    if (phase < 2 && mbar_test(BAR(phase == 0 ? BAR_Q : BAR_O), 0)) ++phase;
                }
                bool take_kv = kv < 16;
                if (take_kv && kv >= NSLOT && !mbar_test(BAR(BAR_EMPTY + kv - NSLOT), 0)) {
                    if (wi < NFILL) take_kv = false;
                    else mbar_wait(BAR(BAR_EMPTY + kv - NSLOT), 0);
                }
                const int i = take_kv ? kv++ : 16 + wi++;
                inflight |= 1u << i;
                const uint32_t fb = BAR(BAR_FULL + i);
                const int h = i & 1;
                if (i == 20) mbar_wait(BAR(BAR_WQFREE), 0);
                mbar_expect_tx(fb, i < 16 ? SLOT_BYTES : HALF_BYTES);
                if (i < 16) {
                    tma_2d(sb + (i % NSLOT) * SLOT_BYTES, i < 8 ? &mp.k : &mp.v, 0, kvline + (i & 7) * 128, fb);
                } else if (i < 18) {
                    tma_2d_keep(sb + OFF_WB + h * HALF_BYTES, &mp.w1, cta * 32, h * 288, fb);
                    tma_2d_keep(sb + OFF_WB + h * HALF_BYTES + HALF_BYTES / 2, &mp.w1, cta * 32, h * 288 + 144, fb);
                } else {
                    tma_2d(sb + (i < 20 ? OFF_WC : OFF_WA) + h * HALF_BYTES, i < 20 ? &mp.w2 : &mp.wo, 0,
                           cta * 288 + h * 144, fb);
                }
                red_add64(&g_prog, 1);
            }
            prog_s[1] = 1;
        } else {
#pragma unroll 1
            for (int i = 0; i < 16; ++i) {
                if (i >= PACE) mbar_wait(BAR(BAR_FULL + i - PACE), 0);
                const uint32_t fb = BAR(BAR_FULL + i);
                const int u = (i >> 1) & 3, h = i & 1;
                if (i >= 8 && u > 0 && h == 0) mbar_wait(BAR(BAR_EMPTY + u - 1), 0);
                mbar_expect_tx(fb, HALF_BYTES);
                if (i < 8) {
                    tma_2d_keep(sb + u * REG_BYTES + h * HALF_BYTES, &mp.w1, (funit + u) * 32, h * 288, fb);
                    tma_2d_keep(sb + u * REG_BYTES + h * HALF_BYTES + HALF_BYTES / 2, &mp.w1, (funit + u) * 32, h * 288 + 144, fb);
                } else {
                    tma_2d(sb + (u == 0 ? 4 : u - 1) * REG_BYTES + h * HALF_BYTES, &mp.w2, 0, (funit + u) * 288 + h * 144, fb);
                }
            }
        }
        return;
    }

    uint32_t xw[9];
    unsigned short xres = 0;
    unsigned long long done0 = 0;
    if (warp < 4) {
        const uint32_t* xp = reinterpret_cast<const uint32_t*>(x) + warp * (DM / 2);
#pragma unroll
        for (int j = 0; j < 9; ++j) xw[j] = __ldg(xp + lane + 32 * j);
    }
    if (cta >= RED0 && warp == 0) {
        const int jr = cta - RED0, pc = lane >> 2, e = lane & 3;
        const int n = 16 * (jr >> 1) + (jr & 1) * 4 + (pc >> 1) + 8 * (e >> 1);
        const int b = 2 * (pc & 1) + (e & 1);
        xres = __ldg(reinterpret_cast<const unsigned short*>(x) + b * DM + n);
    }
    uint32_t cnt_target = 0;
    volatile uint32_t* ep_s = reinterpret_cast<volatile uint32_t*>(smem + OFF_BAR + 304);
    if (warp == 9) {
        if (lane == 2) done0 = ld_rlx64(g_done + (cta % NREP) * 16);
        if (is_att && lane < 2) cnt_target = ld_rlx(g_cnt + cta * 32 + lane);
    }
    asm volatile("bar.sync 0, 352;" ::: "memory");

    if (warp == 10) {
        if (is_att && lane == 0) {
            for (unsigned it = 0; it < SPIN_LIMIT && !prog_s[1]; ++it) {
                prog_s[0] = (int)(ld_rlx64(&g_prog) % (NATT * 21));
                __nanosleep(BAL_SLEEP);
            }
        }
        return;
    }

    if (warp == 9) {
        if (lane == 2) {
            done0 = done0 / NCTA + 1;
            ep_s[4] = (uint32_t)done0 & 3u;
            *reinterpret_cast<volatile unsigned long long*>(smem + OFF_BAR + 312) = done0 * NCTA;
        }
        if (lane < 2) { cnt_target = (cnt_target & ~7u) + 8u; ep_s[lane] = cnt_target; }
        __syncwarp();
        if (lane == 0) mbar_arrive(BAR(BAR_EP));
        const uint32_t ep = ep_s[4];
        if (is_att) {
            mbar_wait(BAR(BAR_WQFREE), 0);
            if (lane == 0) wait_count(g_cnt + cta * 32, cnt_target);
            __syncwarp();
            {
                const uint32_t* src = g_qbox + cta * 256 + lane * 8;
                uint4 v0, v1;
                for (unsigned it = 0; it < SPIN_LIMIT; ++it) {
                    v0 = ld_rlx4(src); v1 = ld_rlx4(src + 4);
                    if (all_set(v0, ep) && all_set(v1, ep)) break;
                }
                *reinterpret_cast<uint4*>(smem + OFF_Q + lane * 16) =
                    make_uint4(__byte_perm(v0.x, v0.y, 0x7632), __byte_perm(v0.z, v0.w, 0x7632),
                               __byte_perm(v1.x, v1.y, 0x7632), __byte_perm(v1.z, v1.w, 0x7632));
                __syncwarp();
                if (lane == 0) mbar_arrive(BAR(BAR_Q));
            }
            mbar_wait(BAR(BAR_FULL + 15), 0);
            if (lane == 1) wait_count(g_cnt + cta * 32 + 1, cnt_target);
            __syncwarp();
            uint32_t* s0 = g_obox + cta * 8 * 64;
            uint32_t* se = s0 + (lane >> 3) * 64 + 32 + (lane & 7);
            uint32_t v[8], e0 = 0, e1 = 0;
            for (unsigned it = 0; it < SPIN_LIMIT; ++it) {
#pragma unroll
                for (int i = 0; i < 8; ++i) v[i] = ld_rlx(s0 + i * 64 + lane);
                e0 = ld_rlx(se); e1 = ld_rlx(se + 4 * 64);
                bool ok = tag_ok(e0, ep) && tag_ok(e1, ep);
#pragma unroll
                for (int i = 0; i < 8; ++i) ok = ok && tag_ok(v[i], ep);
                if (__all_sync(0xffffffffu, ok)) break;
            }
#pragma unroll
            for (int b = 0; b < 4; ++b) {
                const uint32_t e = b < 2 ? e0 : e1;
                const int sl = (b & 1) * 16;
                const float m0 = decf(__shfl_sync(0xffffffffu, e, sl)), l0 = decf(__shfl_sync(0xffffffffu, e, sl + 1));
                const float m1 = decf(__shfl_sync(0xffffffffu, e, sl + 8)), l1 = decf(__shfl_sync(0xffffffffu, e, sl + 9));
                const float M = fmaxf(m0, m1);
                const float f0 = exp2f(m0 - M), f1 = exp2f(m1 - M);
                const float o = __fdividef(decf(v[2 * b]) * f0 + decf(v[2 * b + 1]) * f1, l0 * f0 + l1 * f1);
                reinterpret_cast<__nv_bfloat16*>(smem + OFF_O)[b * APITCH + lane] = __float2bfloat16_rn(o);
            }
            __syncwarp();
            if (lane == 0) mbar_arrive(BAR(BAR_O));
        }
        return;
    }

    const int g = lane >> 2, t = lane & 3;
    float* red = reinterpret_cast<float*>(smem + OFF_RED);

    if (warp < 4) {
        float s = 0.f;
#pragma unroll
        for (int j = 0; j < 9; ++j) s += bf_lo(xw[j]) + bf_hi(xw[j]);
#pragma unroll
        for (int o = 16; o; o >>= 1) s += __shfl_xor_sync(0xffffffffu, s, o);
        const float mean = s * (1.f / DM);
        float v = 0.f;
#pragma unroll
        for (int j = 0; j < 9; ++j) {
            float a = bf_lo(xw[j]) - mean, c = bf_hi(xw[j]) - mean;
            v += a * a + c * c;
        }
#pragma unroll
        for (int o = 16; o; o >>= 1) v += __shfl_xor_sync(0xffffffffu, v, o);
        const float mb = bf16r(mean);
        const float rden = 1.f / bf16r(sqrtf(bf16r(bf16r(v * (1.f / DM)) + 1e-5f)));
        uint32_t* xs = reinterpret_cast<uint32_t*>(smem + OFF_XN + warp * XPITCH * 2);
#pragma unroll
        for (int j = 0; j < 9; ++j)
            xs[lane + 32 * j] = pack_bf16(bf16r(bf_lo(xw[j]) - mb) * rden, bf16r(bf_hi(xw[j]) - mb) * rden);
    }
    cbar();
    mbar_wait(BAR(BAR_EP), 0);
    const uint32_t ep = ep_s[4];

    float acc[5][4] = {};

    if (is_att) {
        mbar_wait(BAR(BAR_FULL + 22 + (warp >> 2)), 0);
        col_gemv(sb + OFF_WA, sb + OFF_XN, red, warp, lane);
        cbar();
        if (tid < 128) {
            const int b = warp;
            const float v = red[lane * 4 + b] + red[(32 + lane) * 4 + b] + red[(64 + lane) * 4 + b] + red[(96 + lane) * 4 + b];
            const uint32_t w = encf(bf16r(v), ep);
            uint32_t* dst = g_qbox + (kvh * 8 + 2 * b) * 256 + rk * 32 + lane;
            st_rlx(dst, w);
            st_rlx(dst + 256, w);
            if (lane < 2) red_add32(g_cnt + (kvh * 8 + 2 * b + lane) * 32, 1);
        }
        if (tid == 0) mbar_arrive(BAR(BAR_WQFREE));
        mbar_wait(BAR(BAR_Q), 0);

        uint4 qa[4];
#pragma unroll
        for (int j = 0; j < 4; ++j) {
            qa[j] = lds128(sb + OFF_Q + (g & 1) * 256 + j * 64 + t * 16);
            if (g >= 2) qa[j] = make_uint4(0, 0, 0, 0);
        }
        float s[8][2];
        {
            const int f = (g >> 1) ^ (2 * (g & 1));
            const uint32_t kb = sb + (warp % NSLOT) * SLOT_BYTES + (4 * (g & 1) + f) * 256;
            uint32_t ko[4];
#pragma unroll
            for (int j = 0; j < 4; ++j) ko[j] = kb + (j >> 1) * 128 + (((4 * (j & 1) + t) ^ (2 * f + (j >> 1))) << 4);
            mbar_wait(BAR(BAR_FULL + warp), 0);
#pragma unroll
            for (int T = 0; T < 8; ++T) {
                float c[4] = {0.f, 0.f, 0.f, 0.f};
#pragma unroll
                for (int j = 0; j < 4; ++j) {
                    const uint4 kv = lds128(ko[j] + T * 2048);
                    mma16816(c, qa[j].x, 0u, qa[j].y, 0u, kv.x, kv.y);
                    mma16816(c, qa[j].z, 0u, qa[j].w, 0u, kv.z, kv.w);
                }
                s[T][0] = c[0];
                s[T][1] = c[1];
            }
            __syncwarp();
            if (lane == 0) mbar_arrive(BAR(BAR_EMPTY + warp));
        }
        const float cs = 0.08838834764831845f * 1.4426950408889634f;
        float m = s[0][0];
#pragma unroll
        for (int T = 0; T < 8; ++T) m = fmaxf(m, fmaxf(s[T][0], s[T][1]));
        m = fmaxf(m, __shfl_xor_sync(0xffffffffu, m, 1));
        m = fmaxf(m, __shfl_xor_sync(0xffffffffu, m, 2));
        const float mc = m * cs;
        float l = 0.f;
        uint32_t pb[8];
#pragma unroll
        for (int T = 0; T < 8; ++T) {
            const float p0 = exp2f(fmaf(s[T][0], cs, -mc)), p1 = exp2f(fmaf(s[T][1], cs, -mc));
            l += p0 + p1;
            pb[T] = pack_bf16(p0, p1);
        }
        l += __shfl_xor_sync(0xffffffffu, l, 1);
        l += __shfl_xor_sync(0xffffffffu, l, 2);
        float2* ml = reinterpret_cast<float2*>(smem + OFF_ML);
        if (g < 2 && t == 0) ml[warp * 2 + g] = make_float2(mc, l);

        {
            const int c = 8 + warp;
            const uint32_t vb = sb + (c % NSLOT) * SLOT_BYTES;
            uint32_t vo[2][2];
#pragma unroll
            for (int e = 0; e < 2; ++e)
#pragma unroll
                for (int hf = 0; hf < 2; ++hf) {
                    const int f = t ^ (2 * e);
                    vo[e][hf] = vb + (4 * e + f) * 256 + hf * 128 + ((g ^ (2 * f + hf)) << 4);
                }
            mbar_wait(BAR(BAR_FULL + c), 0);
            float o[2][4][4] = {};
#pragma unroll
            for (int ks = 0; ks < 4; ++ks) {
#pragma unroll
                for (int hf = 0; hf < 2; ++hf) {
                    const uint4 R0 = lds128(vo[0][hf] + ks * 4096), R1 = lds128(vo[1][hf] + ks * 4096);
                    const uint4 R2 = lds128(vo[0][hf] + ks * 4096 + 2048), R3 = lds128(vo[1][hf] + ks * 4096 + 2048);
                    const uint32_t r0[4] = {R0.x, R0.y, R0.z, R0.w}, r1[4] = {R1.x, R1.y, R1.z, R1.w};
                    const uint32_t r2[4] = {R2.x, R2.y, R2.z, R2.w}, r3[4] = {R3.x, R3.y, R3.z, R3.w};
#pragma unroll
                    for (int j = 0; j < 4; ++j)
                        mma16816(o[hf][j], __byte_perm(r0[j], r1[j], 0x5410), __byte_perm(r0[j], r1[j], 0x7632),
                                 __byte_perm(r2[j], r3[j], 0x5410), __byte_perm(r2[j], r3[j], 0x7632),
                                 pb[2 * ks], pb[2 * ks + 1]);
                }
            }
            __syncwarp();
            if (lane == 0 && c + NSLOT < 16) mbar_arrive(BAR(BAR_EMPTY + c));
            if (t == 0) {
                float* op = reinterpret_cast<float*>(smem + OFF_OP) + warp * 256 + 8 * g;
#pragma unroll
                for (int hf = 0; hf < 2; ++hf)
#pragma unroll
                    for (int jp = 0; jp < 2; ++jp) {
                        *reinterpret_cast<float4*>(op + 64 * hf + 4 * jp) =
                            make_float4(o[hf][2 * jp][0], o[hf][2 * jp][2], o[hf][2 * jp + 1][0], o[hf][2 * jp + 1][2]);
                        *reinterpret_cast<float4*>(op + 128 + 64 * hf + 4 * jp) =
                            make_float4(o[hf][2 * jp][1], o[hf][2 * jp][3], o[hf][2 * jp + 1][1], o[hf][2 * jp + 1][3]);
                    }
            }
        }
        cbar();
        {
            const int head = tid >> 7;
            float M = ml[head].x;
#pragma unroll
            for (int w = 1; w < 8; ++w) M = fmaxf(M, ml[w * 2 + head].x);
            const float* op = reinterpret_cast<const float*>(smem + OFF_OP) + tid;
            float o = 0.f, L = 0.f;
#pragma unroll
            for (int w = 0; w < 8; ++w) {
                const float2 e = ml[w * 2 + head];
                const float f = exp2f(e.x - M);
                o = fmaf(f, op[w * 256], o);
                L = fmaf(f, e.y, L);
            }
            uint32_t* dst = g_obox + ((kvh * 8 + warp) * 8 + rk) * 64;
            st_rlx(dst + lane, encf(o, ep));
            if (lane < 8) st_rlx(dst + 32 + lane, encf((lane & 1) ? L : M, ep));
            if (lane == 0) red_add32(g_cnt + (kvh * 8 + warp) * 32 + 1, 1);
        }
    }

    const int nu = is_att ? 1 : 4;
#pragma unroll 1
    for (int u = 0; u < nu; ++u) {
        float bias = 0.f;
        if (tid < 128) bias = __bfloat162float(b1[(funit + u) * 32 + (tid >> 2)]);
        mbar_wait(BAR(BAR_FULL + (is_att ? 16 : 2 * u) + (warp >> 2)), 0);
        col_gemv(sb + (is_att ? OFF_WB : u * REG_BYTES), sb + OFF_XN, red, warp, lane);
        cbar();
        if (tid == 0 && u < nu - 1) mbar_arrive(BAR(BAR_EMPTY + u));
        if (tid < 128) {
            float h = red[tid] + red[128 + tid] + red[256 + tid] + red[384 + tid];
            h = bf16r(bf16r(h) + bias);
            reinterpret_cast<__nv_bfloat16*>(smem + OFF_ACT + u * 320)[(tid & 3) * APITCH + (tid >> 2)] =
                __float2bfloat16_rn(mish(h));
        }
        cbar();
    }

    const int nr = is_att ? 4 : 8;
#pragma unroll 1
    for (int i = 0; i < nr; ++i) {
        const int u = i >> 1, h = i & 1;
        if (is_att && i == 2) mbar_wait(BAR(BAR_O), 0);
        mbar_wait(BAR(BAR_FULL + (is_att ? 18 : 8) + i), 0);
        if (tid < NREP && i == nr - 1) red_add64(g_done + tid * 16, 1);
        const uint32_t wbase = is_att ? (u ? OFF_WA : OFF_WC) : (u == 0 ? 4 : u - 1) * REG_BYTES;
        const uint32_t vbase = is_att ? (u ? OFF_O : OFF_ACT) : OFF_ACT + u * 320;
        row_gemv16(sb + wbase + h * HALF_BYTES, sb + vbase + h * 32, acc, warp, lane);
    }

    if (t < 2) {
#pragma unroll
        for (int i = 0; i < 5; ++i) {
            if (i < 4 || warp < 4) {
                const int jr = 2 * (warp + 8 * i) + (g >> 2);
                uint32_t* dst = g_part + ((size_t)(jr * NCTA + cta) * 32 + ((g & 3) * 2 + t) * 4);
                st_rlx4(dst, make_uint4(encf(acc[i][0], ep), encf(acc[i][1], ep), encf(acc[i][2], ep), encf(acc[i][3], ep)));
            }
        }
    }

    if (cta >= RED0) {
        const int jr = cta - RED0;
        const int p0 = (lane >> 3) + 4 * warp;
        uint32_t* src = g_part + ((size_t)(jr * NCTA + p0) * 32 + (lane & 7) * 4);
        const bool has4 = p0 + 128 < NCTA;
        uint4 v[5];
        unsigned pend = has4 ? 31u : 15u;
        v[4] = make_uint4(0, 0, 0, 0);
        if (lane == 0) {
            const unsigned long long tgt = *reinterpret_cast<volatile unsigned long long*>(smem + OFF_BAR + 312);
            for (unsigned it = 0; it < SPIN_LIMIT; ++it) {
                const unsigned long long d = ld_rlx64(g_done + (cta % NREP) * 16);
                if (d >= tgt) break;
                if (d + 64 < tgt) __nanosleep(200);
            }
        }
        __syncwarp();
        for (unsigned it = 0; it < SPIN_LIMIT; ++it) {
#pragma unroll
            for (int i = 0; i < 5; ++i)
                if (pend & (1u << i)) v[i] = ld_rlx4(src + i * 32 * 32);
#pragma unroll
            for (int i = 0; i < 5; ++i)
                if ((pend & (1u << i)) && all_set(v[i], ep)) pend &= ~(1u << i);
            if (!pend) break;
        }
        float4 a = make_float4(0.f, 0.f, 0.f, 0.f);
#pragma unroll
        for (int i = 0; i < 5; ++i) {
            a.x += decf(v[i].x); a.y += decf(v[i].y);
            a.z += decf(v[i].z); a.w += decf(v[i].w);
        }
#pragma unroll
        for (int o = 8; o <= 16; o <<= 1) {
            a.x += __shfl_xor_sync(0xffffffffu, a.x, o); a.y += __shfl_xor_sync(0xffffffffu, a.y, o);
            a.z += __shfl_xor_sync(0xffffffffu, a.z, o); a.w += __shfl_xor_sync(0xffffffffu, a.w, o);
        }
        if (lane < 8) *reinterpret_cast<float4*>(red + warp * 32 + lane * 4) = a;
        cbar();
        if (tid < 32) {
            float r = __uint_as_float((uint32_t)xres << 16);
#pragma unroll
            for (int w = 0; w < 8; ++w) r += red[w * 32 + tid];
            const int pc = tid >> 2, e = tid & 3;
            const int n = 16 * (jr >> 1) + (jr & 1) * 4 + (pc >> 1) + 8 * (e >> 1);
            const int b = 2 * (pc & 1) + (e & 1);
            out[b * DM + n] = __float2bfloat16_rn(r);
        }
    }
}

__device__ void fb_layernorm(const __nv_bfloat16* x, float* xn  ) {
    const int warp = threadIdx.x >> 5, lane = threadIdx.x & 31;
    if (warp < NB) {
        float s = 0.f;
        for (int i = lane; i < DM; i += 32) s += __bfloat162float(x[warp * DM + i]);
        for (int o = 16; o; o >>= 1) s += __shfl_xor_sync(0xffffffffu, s, o);
        const float mean = s / DM;
        float v = 0.f;
        for (int i = lane; i < DM; i += 32) { float d = __bfloat162float(x[warp * DM + i]) - mean; v += d * d; }
        for (int o = 16; o; o >>= 1) v += __shfl_xor_sync(0xffffffffu, v, o);
        const float mb = bf16r(mean);
        const float den = bf16r(sqrtf(bf16r(bf16r(v / DM) + 1e-5f)));
        for (int i = lane; i < DM; i += 32)
            xn[warp * DM + i] = bf16r(bf16r(__bfloat162float(x[warp * DM + i]) - mb) / den);
    }
    __syncthreads();
}

__global__ void fb_proj(const __nv_bfloat16* x, const __nv_bfloat16* wq, const __nv_bfloat16* w1,
                        const __nv_bfloat16* b1) {
    __shared__ float xn[NB * DM];
    fb_layernorm(x, xn);
    const int c = blockIdx.x * blockDim.x + threadIdx.x;
    if (c >= QD + FF) return;
    const bool isq = c < QD;
    const __nv_bfloat16* w = isq ? wq + c : w1 + (c - QD);
    const int pitch = isq ? QD : FF;
    float a[NB] = {};
    for (int k = 0; k < DM; ++k) {
        const float wv = __bfloat162float(w[(size_t)k * pitch]);
        for (int b = 0; b < NB; ++b) a[b] = fmaf(xn[b * DM + k], wv, a[b]);
    }
    for (int b = 0; b < NB; ++b) {
        if (isq) g_fb_q[b * QD + c] = __float2bfloat16_rn(a[b]);
        else {
            const float h = bf16r(bf16r(a[b]) + __bfloat162float(b1[c - QD]));
            g_fb_act[b * FF + c - QD] = __float2bfloat16_rn(mish(h));
        }
    }
}

__global__ void fb_attn(const __nv_bfloat16* kc, const __nv_bfloat16* vc) {
    __shared__ float q[DH], p[WIN], rd[128];
    const int b = blockIdx.x / HQ, h = blockIdx.x % HQ, tid = threadIdx.x;
    const size_t base = ((size_t)(b * HKV + h / 2) * SK + (SK - WIN)) * DH;
    q[tid] = __bfloat162float(g_fb_q[b * QD + h * DH + tid]);
    __syncthreads();
    float m = -INFINITY;
    for (int k = tid; k < WIN; k += 128) {
        float s = 0.f;
        for (int d = 0; d < DH; ++d) s = fmaf(q[d], __bfloat162float(kc[base + (size_t)k * DH + d]), s);
        s *= 0.08838834764831845f;
        p[k] = s;
        m = fmaxf(m, s);
    }
    rd[tid] = m;
    __syncthreads();
    for (int i = 0; i < 128; ++i) m = fmaxf(m, rd[i]);
    __syncthreads();
    float l = 0.f;
    for (int k = tid; k < WIN; k += 128) { p[k] = expf(p[k] - m); l += p[k]; }
    rd[tid] = l;
    __syncthreads();
    l = 0.f;
    for (int i = 0; i < 128; ++i) l += rd[i];
    float o = 0.f;
    for (int k = 0; k < WIN; ++k) o = fmaf(p[k], __bfloat162float(vc[base + (size_t)k * DH + tid]), o);
    g_fb_o[b * QD + h * DH + tid] = __float2bfloat16_rn(o / l);
}

__global__ void fb_out(const __nv_bfloat16* x, const __nv_bfloat16* wo, const __nv_bfloat16* w2,
                       __nv_bfloat16* out) {
    __shared__ float rd[8][NB][32];
    const int n = blockIdx.x * 32 + (threadIdx.x & 31), part = threadIdx.x >> 5;
    float a[NB] = {};
    for (int k = part; k < QD; k += 8) {
        const float wv = __bfloat162float(wo[(size_t)k * DM + n]);
        for (int b = 0; b < NB; ++b) a[b] = fmaf(__bfloat162float(g_fb_o[b * QD + k]), wv, a[b]);
    }
    for (int k = part; k < FF; k += 8) {
        const float wv = __bfloat162float(w2[(size_t)k * DM + n]);
        for (int b = 0; b < NB; ++b) a[b] = fmaf(__bfloat162float(g_fb_act[b * FF + k]), wv, a[b]);
    }
    for (int b = 0; b < NB; ++b) rd[part][b][threadIdx.x & 31] = a[b];
    __syncthreads();
    if (threadIdx.x < 128) {
        const int b = threadIdx.x >> 5, c = threadIdx.x & 31;
        float r = __bfloat162float(x[b * DM + blockIdx.x * 32 + c]);
        for (int i = 0; i < 8; ++i) r += rd[i][b][c];
        out[b * DM + blockIdx.x * 32 + c] = __float2bfloat16_rn(r);
    }
}

void launch_fallback(const __nv_bfloat16* x, const __nv_bfloat16* kc, const __nv_bfloat16* vc,
                     const __nv_bfloat16* wq, const __nv_bfloat16* wo, const __nv_bfloat16* w1,
                     const __nv_bfloat16* b1, const __nv_bfloat16* w2, __nv_bfloat16* out) {
    fb_proj<<<(QD + FF) / 128, 128>>>(x, wq, w1, b1);
    fb_attn<<<NB * HQ, 128>>>(kc, vc);
    fb_out<<<DM / 32, 256>>>(x, wo, w2, out);
}

typedef CUresult (*EncodeFn)(CUtensorMap*, CUtensorMapDataType, cuuint32_t, void*, const cuuint64_t*, const cuuint64_t*,
                             const cuuint32_t*, const cuuint32_t*, CUtensorMapInterleave, CUtensorMapSwizzle,
                             CUtensorMapL2promotion, CUtensorMapFloatOOBfill);

#define L2PROMO CU_TENSOR_MAP_L2_PROMOTION_L2_128B

#define L2PROMO2 CU_TENSOR_MAP_L2_PROMOTION_L2_128B
bool make_map(EncodeFn fn, CUtensorMap* m, const void* base, uint64_t cols, uint64_t rows, uint32_t box_cols,
              uint32_t box_rows, CUtensorMapSwizzle sw) {
    cuuint64_t dims[2] = {cols, rows};
    cuuint64_t strides[1] = {cols * 2};
    cuuint32_t box[2] = {box_cols, box_rows};
    cuuint32_t es[2] = {1, 1};
    return fn(m, CU_TENSOR_MAP_DATA_TYPE_BFLOAT16, 2, const_cast<void*>(base), dims, strides, box, es,
              CU_TENSOR_MAP_INTERLEAVE_NONE, sw, box_cols == 32 ? L2PROMO : L2PROMO2, CU_TENSOR_MAP_FLOAT_OOB_FILL_NONE) == CUDA_SUCCESS;
}

struct HostState {
    int ok;
    EncodeFn encode;
    const void* ptr[6];
    bool maps_ok;
    Maps maps;
};
HostState g_host = {-1, nullptr, {nullptr, nullptr, nullptr, nullptr, nullptr, nullptr}, false, {}};

bool fused_ready(const void* wq, const void* kc, const void* vc, const void* w1, const void* w2, const void* wo) {
    HostState& h = g_host;
    if (h.ok < 0) {
        int dev = 0, sms = 0, occ = 0, coop = 0;
        void* fn = nullptr;
        cudaDriverEntryPointQueryResult qr;
        h.ok = 0;
        if (cudaGetDevice(&dev) == cudaSuccess &&
            cudaDeviceGetAttribute(&sms, cudaDevAttrMultiProcessorCount, dev) == cudaSuccess &&
            cudaFuncSetAttribute(fused_kernel, cudaFuncAttributeMaxDynamicSharedMemorySize, SMEM_BYTES) == cudaSuccess &&
            cudaOccupancyMaxActiveBlocksPerMultiprocessor(&occ, fused_kernel, NTHREADS, SMEM_BYTES) == cudaSuccess &&
            sms * occ >= NCTA &&
            cudaDeviceGetAttribute(&coop, cudaDevAttrCooperativeLaunch, dev) == cudaSuccess && coop &&
            cudaGetDriverEntryPoint("cuTensorMapEncodeTiled", &fn, cudaEnableDefault, &qr) == cudaSuccess &&
            qr == cudaDriverEntryPointSuccess && fn) {
            h.encode = (EncodeFn)fn;
            h.ok = 1;
        }
        (void)cudaGetLastError();
    }
    if (h.ok != 1) return false;
    const void* p[6] = {wq, kc, vc, w1, w2, wo};
    bool same = true;
    for (int i = 0; i < 6; ++i) same = same && h.ptr[i] == p[i];
    if (!same) {
        for (int i = 0; i < 6; ++i) h.ptr[i] = p[i];
        const uint64_t kvlines = (uint64_t)NB * HKV * SK * DH / 64;
        h.maps_ok = make_map(h.encode, &h.maps.wq, wq, QD, DM, 32, 144, CU_TENSOR_MAP_SWIZZLE_64B) &&
                    make_map(h.encode, &h.maps.w1, w1, FF, DM, 32, 144, CU_TENSOR_MAP_SWIZZLE_64B) &&
                    make_map(h.encode, &h.maps.k, kc, 64, kvlines, 64, 128, CU_TENSOR_MAP_SWIZZLE_128B) &&
                    make_map(h.encode, &h.maps.v, vc, 64, kvlines, 64, 128, CU_TENSOR_MAP_SWIZZLE_128B) &&
                    make_map(h.encode, &h.maps.w2, w2, 64, (uint64_t)FF * DM / 64, 64, 144, CU_TENSOR_MAP_SWIZZLE_128B) &&
                    make_map(h.encode, &h.maps.wo, wo, 64, (uint64_t)QD * DM / 64, 64, 144, CU_TENSOR_MAP_SWIZZLE_128B);
    }
    return h.maps_ok;
}

}

extern "C" void kernel_launch(void* const* d_in, const int* in_sizes, int n_in, void* d_out, int out_size) {
    const __nv_bfloat16* x = (const __nv_bfloat16*)d_in[0];
    const __nv_bfloat16* kc = (const __nv_bfloat16*)d_in[1];
    const __nv_bfloat16* vc = (const __nv_bfloat16*)d_in[2];
    const __nv_bfloat16* wq = (const __nv_bfloat16*)d_in[3];
    const __nv_bfloat16* wo = (const __nv_bfloat16*)d_in[4];
    const __nv_bfloat16* w1 = (const __nv_bfloat16*)d_in[6];
    const __nv_bfloat16* b1 = (const __nv_bfloat16*)d_in[7];
    const __nv_bfloat16* w2 = (const __nv_bfloat16*)d_in[8];
    __nv_bfloat16* out = (__nv_bfloat16*)d_out;
    if (fused_ready(wq, kc, vc, w1, w2, wo)) {
        cudaLaunchConfig_t cfg = {};
        cfg.gridDim = dim3(NCTA);
        cfg.blockDim = dim3(NTHREADS);
        cfg.dynamicSmemBytes = SMEM_BYTES;
        cfg.stream = 0;
        cudaLaunchAttribute at[1];
        at[0].id = cudaLaunchAttributeCooperative;
        at[0].val.cooperative = 1;
        cfg.attrs = at;
        cfg.numAttrs = 1;
        if (cudaLaunchKernelEx(&cfg, fused_kernel, g_host.maps, x, b1, out) == cudaSuccess) return;
        (void)cudaGetLastError();
    }
    launch_fallback(x, kc, vc, wq, wo, w1, b1, w2, out);
}
```

```cpp
#include <cuda_runtime.h>
#include <cuda.h>
#include <cuda_bf16.h>
#include <stdint.h>

#define DEVINL __device__ __forceinline__

namespace {

constexpr int NB = 4;
constexpr int DM = 576;
constexpr int HQ = 32, HKV = 16, SK = 4096, DH = 128, WIN = 1024;
constexpr int FF = 4608;
constexpr int QD = HQ * DH;

constexpr int NATT = 128;
constexpr int NCTA = 132;
constexpr int NRED = 72;
constexpr int RED0 = NCTA - NRED;
constexpr int NTHREADS = 352;

constexpr int SLOT_BYTES = 16384;
constexpr int NSLOT = 6;
constexpr int REG_BYTES = 36864;
constexpr int HALF_BYTES = REG_BYTES / 2;
constexpr int OFF_WA = NSLOT * SLOT_BYTES;
constexpr int OFF_WB = OFF_WA + REG_BYTES;
constexpr int OFF_WC = OFF_WB + REG_BYTES;
constexpr int OFF_MISC = OFF_WC + REG_BYTES;
constexpr int XPITCH = 584;
constexpr int OFF_XN = OFF_MISC;
constexpr int OFF_RED = OFF_XN + NB * XPITCH * 2;
constexpr int OFF_Q = OFF_RED + 2048;
constexpr int OFF_ACT = OFF_Q + 512;
constexpr int OFF_O = OFF_ACT + 1280;
constexpr int OFF_ML = OFF_O + 320;
constexpr int OFF_BAR = OFF_ML + 128;
constexpr int OFF_OP = OFF_BAR + 352;
constexpr int SMEM_BYTES = OFF_OP + 8192;
static_assert(NSLOT == 6, "see kv_off");
static_assert(SMEM_BYTES <= 232448, "smem");
static_assert(OFF_RED % 16 == 0 && OFF_Q % 16 == 0 && OFF_OP % 16 == 0 && OFF_BAR % 8 == 0, "align");
static_assert(5 * REG_BYTES <= OFF_MISC, "ffn cta regions");
static_assert(OFF_WA % 1024 == 0 && HALF_BYTES % 1024 == 0, "swizzle atom alignment");

constexpr int APITCH = 40;

constexpr int BAR_FULL = 0;
constexpr int BAR_EMPTY = 24;
constexpr int BAR_WQFREE = 34, BAR_Q = 35, BAR_O = 36, BAR_EP = 37, NBAR = 38;

#define PACE_A 4
#define PACE 5
#define PACE_END 3
#define PACE_FIN 3
#define BAL_UP 64
#define BAL_DN 96
#define BAL_SLEEP 100

constexpr unsigned SPIN_LIMIT = 1u << 20;

__device__ __align__(128) uint32_t g_qbox[NATT * 256];
__device__ __align__(128) uint32_t g_obox[NATT * 8 * 64];
__device__ __align__(128) uint32_t g_part[NRED * NCTA * 32];
__device__ __align__(128) uint32_t g_cnt[NATT * 32];
__device__ __align__(128) unsigned long long g_prog_line[16];
#define g_prog g_prog_line[0]
#define NREP 4
__device__ __align__(128) unsigned long long g_done[NREP * 16];

__device__ __nv_bfloat16 g_fb_q[NB * QD];
__device__ __nv_bfloat16 g_fb_act[NB * FF];
__device__ __nv_bfloat16 g_fb_o[NB * QD];

DEVINL uint32_t smem_u32(const void* p) { return (uint32_t)__cvta_generic_to_shared(p); }

DEVINL void mbar_init(uint32_t bar, uint32_t cnt) {
    asm volatile("mbarrier.init.shared::cta.b64 [%0], %1;" ::"r"(bar), "r"(cnt) : "memory");
}
DEVINL void mbar_expect_tx(uint32_t bar, uint32_t bytes) {
    asm volatile("mbarrier.arrive.expect_tx.shared::cta.b64 _, [%0], %1;" ::"r"(bar), "r"(bytes) : "memory");
}
DEVINL void mbar_arrive(uint32_t bar) {
    asm volatile("mbarrier.arrive.shared::cta.b64 _, [%0];" ::"r"(bar) : "memory");
}
DEVINL void mbar_wait(uint32_t bar, uint32_t parity) {
    uint32_t ok = 0;
    for (unsigned it = 0; it < SPIN_LIMIT; ++it) {
        asm volatile(
            "{\n\t.reg .pred p;\n\t"
            "mbarrier.try_wait.parity.shared::cta.b64 p, [%1], %2;\n\t"
            "selp.u32 %0, 1, 0, p;\n\t}"
            : "=r"(ok) : "r"(bar), "r"(parity) : "memory");
        if (ok) break;
    }
}
DEVINL bool mbar_test(uint32_t bar, uint32_t parity) {
    uint32_t ok;
    asm volatile(
        "{\n\t.reg .pred p;\n\t"
        "mbarrier.test_wait.parity.shared::cta.b64 p, [%1], %2;\n\t"
        "selp.u32 %0, 1, 0, p;\n\t}"
        : "=r"(ok) : "r"(bar), "r"(parity) : "memory");
    return ok != 0;
}
DEVINL void tma_2d(uint32_t dst, const CUtensorMap* map, int c0, int c1, uint32_t bar) {
    asm volatile(
        "{\n\t.reg .b64 pol;\n\t"
        "createpolicy.fractional.L2::evict_first.b64 pol, 1.0;\n\t"
        "cp.async.bulk.tensor.2d.shared::cluster.global.mbarrier::complete_tx::bytes.L2::cache_hint [%0], [%1, {%2, %3}], [%4], pol;\n\t}"
        ::"r"(dst), "l"(map), "r"(c0), "r"(c1), "r"(bar) : "memory");
}
DEVINL void tma_2d_keep(uint32_t dst, const CUtensorMap* map, int c0, int c1, uint32_t bar) {
    asm volatile(
        "cp.async.bulk.tensor.2d.shared::cluster.global.mbarrier::complete_tx::bytes [%0], [%1, {%2, %3}], [%4];"
        ::"r"(dst), "l"(map), "r"(c0), "r"(c1), "r"(bar) : "memory");
}
DEVINL void prefetch_tmap(const CUtensorMap* map) {
    asm volatile("prefetch.tensormap [%0];" ::"l"(map) : "memory");
}
DEVINL void cbar() { asm volatile("bar.sync 1, 256;" ::: "memory"); }

DEVINL void ldsm4t(uint32_t addr, uint32_t& r0, uint32_t& r1, uint32_t& r2, uint32_t& r3) {
    asm volatile("ldmatrix.sync.aligned.m8n8.x4.trans.shared.b16 {%0,%1,%2,%3}, [%4];"
                 : "=r"(r0), "=r"(r1), "=r"(r2), "=r"(r3) : "r"(addr) : "memory");
}
DEVINL uint4 lds128(uint32_t addr) {
    uint4 v;
    asm volatile("ld.shared.v4.u32 {%0,%1,%2,%3}, [%4];" : "=r"(v.x), "=r"(v.y), "=r"(v.z), "=r"(v.w) : "r"(addr) : "memory");
    return v;
}
DEVINL uint32_t lds32(uint32_t addr) {
    uint32_t v;
    asm volatile("ld.shared.u32 %0, [%1];" : "=r"(v) : "r"(addr) : "memory");
    return v;
}
DEVINL void mma16816(float* c, uint32_t a0, uint32_t a1, uint32_t a2, uint32_t a3, uint32_t b0, uint32_t b1) {
    asm volatile(
        "mma.sync.aligned.m16n8k16.row.col.f32.bf16.bf16.f32 {%0,%1,%2,%3}, {%4,%5,%6,%7}, {%8,%9}, {%0,%1,%2,%3};"
        : "+f"(c[0]), "+f"(c[1]), "+f"(c[2]), "+f"(c[3])
        : "r"(a0), "r"(a1), "r"(a2), "r"(a3), "r"(b0), "r"(b1));
}
DEVINL uint32_t pack_bf16(float lo, float hi) {
    uint32_t r;
    asm("cvt.rn.bf16x2.f32 %0, %1, %2;" : "=r"(r) : "f"(hi), "f"(lo));
    return r;
}
DEVINL float bf16r(float x) { return __bfloat162float(__float2bfloat16_rn(x)); }
DEVINL float bf_lo(uint32_t w) { return __uint_as_float(w << 16); }
DEVINL float bf_hi(uint32_t w) { return __uint_as_float(w & 0xffff0000u); }

DEVINL uint32_t encf(float f, uint32_t ep) { return (__float_as_uint(f) & ~3u) | ep; }
DEVINL bool tag_ok(uint32_t w, uint32_t ep) { return (w & 3u) == ep; }
DEVINL float decf(uint32_t w) { return __uint_as_float(w & ~3u); }
DEVINL void st_rlx(uint32_t* p, uint32_t v) {
    asm volatile("st.relaxed.gpu.global.u32 [%0], %1;" ::"l"(p), "r"(v) : "memory");
}
DEVINL void st_rlx4(uint32_t* p, uint4 v) {
    asm volatile("st.relaxed.gpu.global.v4.u32 [%0], {%1,%2,%3,%4};" ::"l"(p), "r"(v.x), "r"(v.y), "r"(v.z), "r"(v.w) : "memory");
}
DEVINL uint32_t ld_rlx(const uint32_t* p) {
    uint32_t v;
    asm volatile("ld.relaxed.gpu.global.u32 %0, [%1];" : "=r"(v) : "l"(p) : "memory");
    return v;
}
DEVINL uint4 ld_rlx4(const uint32_t* p) {
    uint4 v;
    asm volatile("ld.relaxed.gpu.global.v4.u32 {%0,%1,%2,%3}, [%4];" : "=r"(v.x), "=r"(v.y), "=r"(v.z), "=r"(v.w) : "l"(p) : "memory");
    return v;
}
DEVINL unsigned long long ld_rlx64(const unsigned long long* p) {
    unsigned long long v;
    asm volatile("ld.relaxed.gpu.global.u64 %0, [%1];" : "=l"(v) : "l"(p) : "memory");
    return v;
}
DEVINL void red_add64(unsigned long long* p, unsigned long long v) {
    asm volatile("red.relaxed.gpu.global.add.u64 [%0], %1;" ::"l"(p), "l"(v) : "memory");
}
DEVINL void red_add32(uint32_t* p, uint32_t v) {
    asm volatile("red.relaxed.gpu.global.add.u32 [%0], %1;" ::"l"(p), "r"(v) : "memory");
}
DEVINL void wait_count(const uint32_t* p, uint32_t target) {
    for (unsigned it = 0; it < SPIN_LIMIT; ++it)
        if ((int)(ld_rlx(p) - target) >= 0) break;
}
DEVINL bool all_set(uint4 v, uint32_t ep) { return (((v.x ^ ep) | (v.y ^ ep) | (v.z ^ ep) | (v.w ^ ep)) & 3u) == 0; }

DEVINL float mish(float h) {
    float sp = log1pf(expf(-fabsf(h))) + fmaxf(h, 0.f);
    return h * tanhf(sp);
}

DEVINL void col_gemv(uint32_t wbase, uint32_t xn_s, float* red, int warp, int lane) {
    const int mt = warp & 1, kg = warp >> 1;
    const int g = lane >> 2, t = lane & 3;
    const int j = lane >> 3, r = lane & 7;
    const int chunk = 2 * mt + (j & 1);
    const uint32_t aaddr = wbase + (kg * 144 + (j >> 1) * 8 + r) * 64 + ((chunk ^ ((r >> 1) & 3)) << 4);
    const uint32_t baddr = xn_s + ((g & 3) * XPITCH + kg * 144 + 2 * t) * 2;
    float acc[3][4] = {};
#pragma unroll
    for (int ks = 0; ks < 9; ++ks) {
        uint32_t a0, a1, a2, a3;
        ldsm4t(aaddr + ks * 1024, a0, a1, a2, a3);
        uint32_t b0 = lds32(baddr + ks * 32), b1 = lds32(baddr + ks * 32 + 16);
        if (g >= 4) { b0 = 0; b1 = 0; }
        mma16816(acc[ks % 3], a0, a1, a2, a3, b0, b1);
    }
    if (t < 2) {
        float2 v0 = make_float2(acc[0][0] + acc[1][0] + acc[2][0], acc[0][1] + acc[1][1] + acc[2][1]);
        float2 v1 = make_float2(acc[0][2] + acc[1][2] + acc[2][2], acc[0][3] + acc[1][3] + acc[2][3]);
        *reinterpret_cast<float2*>(red + (kg * 32 + 16 * mt + g) * 4 + 2 * t) = v0;
        *reinterpret_cast<float2*>(red + (kg * 32 + 16 * mt + g + 8) * 4 + 2 * t) = v1;
    }
}

DEVINL void row_gemv16(uint32_t wbase, uint32_t v_s, float (&acc)[5][4], int warp, int lane) {
    const int g = lane >> 2, t = lane & 3;
    const int j = lane >> 3, r = lane & 7;
    const int nb = 2 * warp + (j & 1);
    const int line0 = ((j >> 1) * 8 + r) * 9 + (nb >> 3);
    const uint32_t baddr = v_s + ((g & 3) * APITCH + 2 * t) * 2;
    uint32_t b0 = lds32(baddr), b1 = lds32(baddr + 16);
    if (g >= 4) { b0 = 0; b1 = 0; }
#pragma unroll
    for (int i = 0; i < 5; ++i) {
        if (i < 4 || warp < 4) {
            const int line = line0 + 2 * i;
            uint32_t a0, a1, a2, a3;
            ldsm4t(wbase + line * 128 + (((nb ^ line) & 7) << 4), a0, a1, a2, a3);
            mma16816(acc[i], a0, a1, a2, a3, b0, b1);
        }
    }
}

DEVINL uint32_t kv_off(int c) {
    return c < 6 ? c * SLOT_BYTES : (c < 8 ? OFF_WC + (c - 6) * HALF_BYTES : (c < 14 ? c - 8 : c - 14) * SLOT_BYTES);
}

struct Maps { CUtensorMap wq, k, v, w1, w2, wo; };

__global__ void __launch_bounds__(NTHREADS, 1)
fused_kernel(const __grid_constant__ Maps mp, const __nv_bfloat16* __restrict__ x,
             const __nv_bfloat16* __restrict__ b1, __nv_bfloat16* __restrict__ out) {
    extern __shared__ __align__(1024) unsigned char smem[];
    const uint32_t sb = smem_u32(smem);
    const int tid = threadIdx.x, warp = tid >> 5, lane = tid & 31;
    const int cta = blockIdx.x;
    const bool is_att = cta < NATT;
    const int kvh = cta >> 3, rk = cta & 7;
    const uint32_t bars = sb + OFF_BAR;
    auto BAR = [&](int i) { return bars + 8u * i; };
    const int funit = is_att ? cta : NATT + (cta - NATT) * 4;
    const int kvline = (((rk >> 1) * HKV + kvh) * SK + (SK - WIN) + (rk & 1) * (WIN / 2)) * 2;

    if (tid == 256) {
        prefetch_tmap(&mp.wq);
        prefetch_tmap(&mp.k);
        mbar_init(BAR(0), 1); mbar_init(BAR(22), 1); mbar_init(BAR(23), 1);
        asm volatile("fence.mbarrier_init.release.cluster;" ::: "memory");
        if (is_att) {
#pragma unroll
            for (int h = 0; h < 2; ++h) {
                mbar_expect_tx(BAR(22 + h), HALF_BYTES);
                tma_2d_keep(sb + OFF_WA + h * HALF_BYTES, &mp.wq, cta * 32, h * 288, BAR(22 + h));
                tma_2d_keep(sb + OFF_WA + h * HALF_BYTES + HALF_BYTES / 2, &mp.wq, cta * 32, h * 288 + 144, BAR(22 + h));
            }
            mbar_expect_tx(BAR(0), SLOT_BYTES);
            tma_2d(sb, &mp.k, 0, kvline, BAR(0));
        }
#pragma unroll
        for (int i = 1; i < NBAR; ++i)
            if (i != 22 && i != 23) mbar_init(BAR(i), 1);
        asm volatile("fence.mbarrier_init.release.cluster;" ::: "memory");
        prefetch_tmap(&mp.w1);
        prefetch_tmap(&mp.v);
        prefetch_tmap(&mp.w2);
        prefetch_tmap(&mp.wo);
        reinterpret_cast<volatile int*>(smem + OFF_BAR + 336)[0] = 0;
        reinterpret_cast<volatile int*>(smem + OFF_BAR + 336)[1] = 0;
    }
    volatile int* prog_s = reinterpret_cast<volatile int*>(smem + OFF_BAR + 336);
    if (warp == 8) {
        __syncwarp();
        asm volatile("bar.arrive 0, 352;" ::: "memory");
        if (lane != 0) return;
        if (is_att) {
            int phase = 0;
            uint32_t inflight = (1u << 22) | (1u << 23) | 1u;
#pragma unroll 1
            for (int i = 1; i < 22; ++i) {
                for (unsigned it = 0; it < SPIN_LIMIT; ++it) {
                    int pace = phase == 0 ? PACE_A : (i < 16 ? PACE : (phase == 1 ? PACE_END : PACE_FIN));
                    const int lag = *prog_s - (i - 1) * NATT;
                    pace += lag >= 2 * BAL_UP ? 2 : (lag >= BAL_UP ? 1 : (lag <= -BAL_DN ? -1 : 0));
                    pace = max(pace, 2);
                    if (__popc(inflight) < pace) break;
                    for (uint32_t rem = inflight; rem; rem &= rem - 1) {
                        const int id = __ffs(rem) - 1;
                        if (mbar_test(BAR(BAR_FULL + id), 0)) inflight &= ~(1u << id);
                    }
                    if (phase < 2 && mbar_test(BAR(phase == 0 ? BAR_Q : BAR_O), 0)) ++phase;
                }
                if (i >= 8 && i < 16) mbar_wait(BAR(BAR_EMPTY + (i < 14 ? i - 8 : i - 6)), 0);
                if (i == 18 || i == 19) mbar_wait(BAR(BAR_EMPTY + i - 12), 0);
                if (i == 20) mbar_wait(BAR(BAR_WQFREE), 0);
                inflight |= 1u << i;
                const uint32_t fb = BAR(BAR_FULL + i);
                const int h = i & 1;
                mbar_expect_tx(fb, i < 16 ? SLOT_BYTES : HALF_BYTES);
                if (i < 16) {
                    tma_2d(sb + kv_off(i), i < 8 ? &mp.k : &mp.v, 0, kvline + (i & 7) * 128, fb);
                } else if (i < 18) {
                    tma_2d_keep(sb + OFF_WB + h * HALF_BYTES, &mp.w1, cta * 32, h * 288, fb);
                    tma_2d_keep(sb + OFF_WB + h * HALF_BYTES + HALF_BYTES / 2, &mp.w1, cta * 32, h * 288 + 144, fb);
                } else {
                    tma_2d(sb + (i < 20 ? OFF_WC : OFF_WA) + h * HALF_BYTES, i < 20 ? &mp.w2 : &mp.wo, 0,
                           cta * 288 + h * 144, fb);
                }
                red_add64(&g_prog, 1);
            }
            prog_s[1] = 1;
        } else {
#pragma unroll 1
            for (int i = 0; i < 16; ++i) {
                if (i >= PACE) mbar_wait(BAR(BAR_FULL + i - PACE), 0);
                const uint32_t fb = BAR(BAR_FULL + i);
                const int u = (i >> 1) & 3, h = i & 1;
                if (i >= 8 && u > 0 && h == 0) mbar_wait(BAR(BAR_EMPTY + u - 1), 0);
                mbar_expect_tx(fb, HALF_BYTES);
                if (i < 8) {
                    tma_2d_keep(sb + u * REG_BYTES + h * HALF_BYTES, &mp.w1, (funit + u) * 32, h * 288, fb);
                    tma_2d_keep(sb + u * REG_BYTES + h * HALF_BYTES + HALF_BYTES / 2, &mp.w1, (funit + u) * 32, h * 288 + 144, fb);
                } else {
                    tma_2d(sb + (u == 0 ? 4 : u - 1) * REG_BYTES + h * HALF_BYTES, &mp.w2, 0, (funit + u) * 288 + h * 144, fb);
                }
            }
        }
        return;
    }

    uint32_t xw[9];
    unsigned short xres = 0;
    unsigned long long done0 = 0;
    if (warp < 4) {
        const uint32_t* xp = reinterpret_cast<const uint32_t*>(x) + warp * (DM / 2);
#pragma unroll
        for (int j = 0; j < 9; ++j) xw[j] = __ldg(xp + lane + 32 * j);
    }
    if (cta >= RED0 && warp == 0) {
        const int jr = cta - RED0, pc = lane >> 2, e = lane & 3;
        const int n = 16 * (jr >> 1) + (jr & 1) * 4 + (pc >> 1) + 8 * (e >> 1);
        const int b = 2 * (pc & 1) + (e & 1);
        xres = __ldg(reinterpret_cast<const unsigned short*>(x) + b * DM + n);
    }
    uint32_t cnt_target = 0;
    volatile uint32_t* ep_s = reinterpret_cast<volatile uint32_t*>(smem + OFF_BAR + 304);
    if (warp == 9) {
        if (lane == 2) done0 = ld_rlx64(g_done + (cta % NREP) * 16);
        if (is_att && lane < 2) cnt_target = ld_rlx(g_cnt + cta * 32 + lane);
    }
    asm volatile("bar.sync 0, 352;" ::: "memory");

    if (warp == 10) {
        if (is_att && lane == 0) {
            for (unsigned it = 0; it < SPIN_LIMIT && !prog_s[1]; ++it) {
                prog_s[0] = (int)(ld_rlx64(&g_prog) % (NATT * 21));
                __nanosleep(BAL_SLEEP);
            }
        }
        return;
    }

    if (warp == 9) {
        if (lane == 2) {
            done0 = done0 / NCTA + 1;
            ep_s[4] = (uint32_t)done0 & 3u;
            *reinterpret_cast<volatile unsigned long long*>(smem + OFF_BAR + 312) = done0 * NCTA;
        }
        if (lane < 2) { cnt_target = (cnt_target & ~7u) + 8u; ep_s[lane] = cnt_target; }
        __syncwarp();
        if (lane == 0) mbar_arrive(BAR(BAR_EP));
        const uint32_t ep = ep_s[4];
        if (is_att) {
            mbar_wait(BAR(BAR_WQFREE), 0);
            if (lane == 0) wait_count(g_cnt + cta * 32, cnt_target);
            __syncwarp();
            {
                const uint32_t* src = g_qbox + cta * 256 + lane * 8;
                uint4 v0, v1;
                for (unsigned it = 0; it < SPIN_LIMIT; ++it) {
                    v0 = ld_rlx4(src); v1 = ld_rlx4(src + 4);
                    if (all_set(v0, ep) && all_set(v1, ep)) break;
                }
                *reinterpret_cast<uint4*>(smem + OFF_Q + lane * 16) =
                    make_uint4(__byte_perm(v0.x, v0.y, 0x7632), __byte_perm(v0.z, v0.w, 0x7632),
                               __byte_perm(v1.x, v1.y, 0x7632), __byte_perm(v1.z, v1.w, 0x7632));
                __syncwarp();
                if (lane == 0) mbar_arrive(BAR(BAR_Q));
            }
            mbar_wait(BAR(BAR_FULL + 15), 0);
            if (lane == 1) wait_count(g_cnt + cta * 32 + 1, cnt_target);
            __syncwarp();
            uint32_t* s0 = g_obox + cta * 8 * 64;
            uint32_t* se = s0 + (lane >> 3) * 64 + 32 + (lane & 7);
            uint32_t v[8], e0 = 0, e1 = 0;
            for (unsigned it = 0; it < SPIN_LIMIT; ++it) {
#pragma unroll
                for (int i = 0; i < 8; ++i) v[i] = ld_rlx(s0 + i * 64 + lane);
                e0 = ld_rlx(se); e1 = ld_rlx(se + 4 * 64);
                bool ok = tag_ok(e0, ep) && tag_ok(e1, ep);
#pragma unroll
                for (int i = 0; i < 8; ++i) ok = ok && tag_ok(v[i], ep);
                if (__all_sync(0xffffffffu, ok)) break;
            }
#pragma unroll
            for (int b = 0; b < 4; ++b) {
                const uint32_t e = b < 2 ? e0 : e1;
                const int sl = (b & 1) * 16;
                const float m0 = decf(__shfl_sync(0xffffffffu, e, sl)), l0 = decf(__shfl_sync(0xffffffffu, e, sl + 1));
                const float m1 = decf(__shfl_sync(0xffffffffu, e, sl + 8)), l1 = decf(__shfl_sync(0xffffffffu, e, sl + 9));
                const float M = fmaxf(m0, m1);
                const float f0 = exp2f(m0 - M), f1 = exp2f(m1 - M);
                const float o = __fdividef(decf(v[2 * b]) * f0 + decf(v[2 * b + 1]) * f1, l0 * f0 + l1 * f1);
                reinterpret_cast<__nv_bfloat16*>(smem + OFF_O)[b * APITCH + lane] = __float2bfloat16_rn(o);
            }
            __syncwarp();
            if (lane == 0) mbar_arrive(BAR(BAR_O));
        }
        return;
    }

    const int g = lane >> 2, t = lane & 3;
    float* red = reinterpret_cast<float*>(smem + OFF_RED);

    if (warp < 4) {
        float s = 0.f;
#pragma unroll
        for (int j = 0; j < 9; ++j) s += bf_lo(xw[j]) + bf_hi(xw[j]);
#pragma unroll
        for (int o = 16; o; o >>= 1) s += __shfl_xor_sync(0xffffffffu, s, o);
        const float mean = s * (1.f / DM);
        float v = 0.f;
#pragma unroll
        for (int j = 0; j < 9; ++j) {
            float a = bf_lo(xw[j]) - mean, c = bf_hi(xw[j]) - mean;
            v += a * a + c * c;
        }
#pragma unroll
        for (int o = 16; o; o >>= 1) v += __shfl_xor_sync(0xffffffffu, v, o);
        const float mb = bf16r(mean);
        const float rden = 1.f / bf16r(sqrtf(bf16r(bf16r(v * (1.f / DM)) + 1e-5f)));
        uint32_t* xs = reinterpret_cast<uint32_t*>(smem + OFF_XN + warp * XPITCH * 2);
#pragma unroll
        for (int j = 0; j < 9; ++j)
            xs[lane + 32 * j] = pack_bf16(bf16r(bf_lo(xw[j]) - mb) * rden, bf16r(bf_hi(xw[j]) - mb) * rden);
    }
    cbar();
    mbar_wait(BAR(BAR_EP), 0);
    const uint32_t ep = ep_s[4];

    float acc[5][4] = {};

    if (is_att) {
        mbar_wait(BAR(BAR_FULL + 22 + (warp >> 2)), 0);
        col_gemv(sb + OFF_WA, sb + OFF_XN, red, warp, lane);
        cbar();
        if (tid < 128) {
            const int b = warp;
            const float v = red[lane * 4 + b] + red[(32 + lane) * 4 + b] + red[(64 + lane) * 4 + b] + red[(96 + lane) * 4 + b];
            const uint32_t w = encf(bf16r(v), ep);
            uint32_t* dst = g_qbox + (kvh * 8 + 2 * b) * 256 + rk * 32 + lane;
            st_rlx(dst, w);
            st_rlx(dst + 256, w);
            if (lane < 2) red_add32(g_cnt + (kvh * 8 + 2 * b + lane) * 32, 1);
        }
        if (tid == 0) mbar_arrive(BAR(BAR_WQFREE));
        mbar_wait(BAR(BAR_Q), 0);

        uint4 qa[4];
#pragma unroll
        for (int j = 0; j < 4; ++j) {
            qa[j] = lds128(sb + OFF_Q + (g & 1) * 256 + j * 64 + t * 16);
            if (g >= 2) qa[j] = make_uint4(0, 0, 0, 0);
        }
        float s[8][2];
        {
            const int f = (g >> 1) ^ (2 * (g & 1));
            const uint32_t kb = sb + kv_off(warp) + (4 * (g & 1) + f) * 256;
            uint32_t ko[4];
#pragma unroll
            for (int j = 0; j < 4; ++j) ko[j] = kb + (j >> 1) * 128 + (((4 * (j & 1) + t) ^ (2 * f + (j >> 1))) << 4);
            mbar_wait(BAR(BAR_FULL + warp), 0);
#pragma unroll
            for (int T = 0; T < 8; ++T) {
                float c[4] = {0.f, 0.f, 0.f, 0.f};
#pragma unroll
                for (int j = 0; j < 4; ++j) {
                    const uint4 kv = lds128(ko[j] + T * 2048);
                    mma16816(c, qa[j].x, 0u, qa[j].y, 0u, kv.x, kv.y);
                    mma16816(c, qa[j].z, 0u, qa[j].w, 0u, kv.z, kv.w);
                }
                s[T][0] = c[0];
                s[T][1] = c[1];
            }
            __syncwarp();
            if (lane == 0) mbar_arrive(BAR(BAR_EMPTY + warp));
        }
        const float cs = 0.08838834764831845f * 1.4426950408889634f;
        float m = s[0][0];
#pragma unroll
        for (int T = 0; T < 8; ++T) m = fmaxf(m, fmaxf(s[T][0], s[T][1]));
        m = fmaxf(m, __shfl_xor_sync(0xffffffffu, m, 1));
        m = fmaxf(m, __shfl_xor_sync(0xffffffffu, m, 2));
        const float mc = m * cs;
        float l = 0.f;
        uint32_t pb[8];
#pragma unroll
        for (int T = 0; T < 8; ++T) {
            const float p0 = exp2f(fmaf(s[T][0], cs, -mc)), p1 = exp2f(fmaf(s[T][1], cs, -mc));
            l += p0 + p1;
            pb[T] = pack_bf16(p0, p1);
        }
        l += __shfl_xor_sync(0xffffffffu, l, 1);
        l += __shfl_xor_sync(0xffffffffu, l, 2);
        float2* ml = reinterpret_cast<float2*>(smem + OFF_ML);
        if (g < 2 && t == 0) ml[warp * 2 + g] = make_float2(mc, l);

        {
            const int c = 8 + warp;
            const uint32_t vb = sb + kv_off(c);
            uint32_t vo[2][2];
#pragma unroll
            for (int e = 0; e < 2; ++e)
#pragma unroll
                for (int hf = 0; hf < 2; ++hf) {
                    const int f = t ^ (2 * e);
                    vo[e][hf] = vb + (4 * e + f) * 256 + hf * 128 + ((g ^ (2 * f + hf)) << 4);
                }
            mbar_wait(BAR(BAR_FULL + c), 0);
            float o[2][4][4] = {};
#pragma unroll
            for (int ks = 0; ks < 4; ++ks) {
#pragma unroll
                for (int hf = 0; hf < 2; ++hf) {
                    const uint4 R0 = lds128(vo[0][hf] + ks * 4096), R1 = lds128(vo[1][hf] + ks * 4096);
                    const uint4 R2 = lds128(vo[0][hf] + ks * 4096 + 2048), R3 = lds128(vo[1][hf] + ks * 4096 + 2048);
                    const uint32_t r0[4] = {R0.x, R0.y, R0.z, R0.w}, r1[4] = {R1.x, R1.y, R1.z, R1.w};
                    const uint32_t r2[4] = {R2.x, R2.y, R2.z, R2.w}, r3[4] = {R3.x, R3.y, R3.z, R3.w};
#pragma unroll
                    for (int j = 0; j < 4; ++j)
                        mma16816(o[hf][j], __byte_perm(r0[j], r1[j], 0x5410), __byte_perm(r0[j], r1[j], 0x7632),
                                 __byte_perm(r2[j], r3[j], 0x5410), __byte_perm(r2[j], r3[j], 0x7632),
                                 pb[2 * ks], pb[2 * ks + 1]);
                }
            }
            __syncwarp();
            if (lane == 0 && c + NSLOT < 16) mbar_arrive(BAR(BAR_EMPTY + c));
            if (t == 0) {
                float* op = reinterpret_cast<float*>(smem + OFF_OP) + warp * 256 + 8 * g;
#pragma unroll
                for (int hf = 0; hf < 2; ++hf)
#pragma unroll
                    for (int jp = 0; jp < 2; ++jp) {
                        *reinterpret_cast<float4*>(op + 64 * hf + 4 * jp) =
                            make_float4(o[hf][2 * jp][0], o[hf][2 * jp][2], o[hf][2 * jp + 1][0], o[hf][2 * jp + 1][2]);
                        *reinterpret_cast<float4*>(op + 128 + 64 * hf + 4 * jp) =
                            make_float4(o[hf][2 * jp][1], o[hf][2 * jp][3], o[hf][2 * jp + 1][1], o[hf][2 * jp + 1][3]);
                    }
            }
        }
        cbar();
        {
            const int head = tid >> 7;
            float M = ml[head].x;
#pragma unroll
            for (int w = 1; w < 8; ++w) M = fmaxf(M, ml[w * 2 + head].x);
            const float* op = reinterpret_cast<const float*>(smem + OFF_OP) + tid;
            float o = 0.f, L = 0.f;
#pragma unroll
            for (int w = 0; w < 8; ++w) {
                const float2 e = ml[w * 2 + head];
                const float f = exp2f(e.x - M);
                o = fmaf(f, op[w * 256], o);
                L = fmaf(f, e.y, L);
            }
            uint32_t* dst = g_obox + ((kvh * 8 + warp) * 8 + rk) * 64;
            st_rlx(dst + lane, encf(o, ep));
            if (lane < 8) st_rlx(dst + 32 + lane, encf((lane & 1) ? L : M, ep));
            if (lane == 0) red_add32(g_cnt + (kvh * 8 + warp) * 32 + 1, 1);
        }
    }

    const int nu = is_att ? 1 : 4;
#pragma unroll 1
    for (int u = 0; u < nu; ++u) {
        float bias = 0.f;
        if (tid < 128) bias = __bfloat162float(b1[(funit + u) * 32 + (tid >> 2)]);
        mbar_wait(BAR(BAR_FULL + (is_att ? 16 : 2 * u) + (warp >> 2)), 0);
        col_gemv(sb + (is_att ? OFF_WB : u * REG_BYTES), sb + OFF_XN, red, warp, lane);
        cbar();
        if (tid == 0 && u < nu - 1) mbar_arrive(BAR(BAR_EMPTY + u));
        if (tid < 128) {
            float h = red[tid] + red[128 + tid] + red[256 + tid] + red[384 + tid];
            h = bf16r(bf16r(h) + bias);
            reinterpret_cast<__nv_bfloat16*>(smem + OFF_ACT + u * 320)[(tid & 3) * APITCH + (tid >> 2)] =
                __float2bfloat16_rn(mish(h));
        }
        cbar();
    }

    const int nr = is_att ? 4 : 8;
#pragma unroll 1
    for (int i = 0; i < nr; ++i) {
        const int u = i >> 1, h = i & 1;
        if (is_att && i == 2) mbar_wait(BAR(BAR_O), 0);
        mbar_wait(BAR(BAR_FULL + (is_att ? 18 : 8) + i), 0);
        if (tid < NREP && i == nr - 1) red_add64(g_done + tid * 16, 1);
        const uint32_t wbase = is_att ? (u ? OFF_WA : OFF_WC) : (u == 0 ? 4 : u - 1) * REG_BYTES;
        const uint32_t vbase = is_att ? (u ? OFF_O : OFF_ACT) : OFF_ACT + u * 320;
        row_gemv16(sb + wbase + h * HALF_BYTES, sb + vbase + h * 32, acc, warp, lane);
    }

    if (t < 2) {
#pragma unroll
        for (int i = 0; i < 5; ++i) {
            if (i < 4 || warp < 4) {
                const int jr = 2 * (warp + 8 * i) + (g >> 2);
                uint32_t* dst = g_part + ((size_t)(jr * NCTA + cta) * 32 + ((g & 3) * 2 + t) * 4);
                st_rlx4(dst, make_uint4(encf(acc[i][0], ep), encf(acc[i][1], ep), encf(acc[i][2], ep), encf(acc[i][3], ep)));
            }
        }
    }

    if (cta >= RED0) {
        const int jr = cta - RED0;
        const int p0 = (lane >> 3) + 4 * warp;
        uint32_t* src = g_part + ((size_t)(jr * NCTA + p0) * 32 + (lane & 7) * 4);
        const bool has4 = p0 + 128 < NCTA;
        uint4 v[5];
        unsigned pend = has4 ? 31u : 15u;
        v[4] = make_uint4(0, 0, 0, 0);
        if (lane == 0) {
            const unsigned long long tgt = *reinterpret_cast<volatile unsigned long long*>(smem + OFF_BAR + 312);
            for (unsigned it = 0; it < SPIN_LIMIT; ++it) {
                const unsigned long long d = ld_rlx64(g_done + (cta % NREP) * 16);
                if (d >= tgt) break;
                if (d + 64 < tgt) __nanosleep(200);
            }
        }
        __syncwarp();
        for (unsigned it = 0; it < SPIN_LIMIT; ++it) {
#pragma unroll
            for (int i = 0; i < 5; ++i)
                if (pend & (1u << i)) v[i] = ld_rlx4(src + i * 32 * 32);
#pragma unroll
            for (int i = 0; i < 5; ++i)
                if ((pend & (1u << i)) && all_set(v[i], ep)) pend &= ~(1u << i);
            if (!pend) break;
        }
        float4 a = make_float4(0.f, 0.f, 0.f, 0.f);
#pragma unroll
        for (int i = 0; i < 5; ++i) {
            a.x += decf(v[i].x); a.y += decf(v[i].y);
            a.z += decf(v[i].z); a.w += decf(v[i].w);
        }
#pragma unroll
        for (int o = 8; o <= 16; o <<= 1) {
            a.x += __shfl_xor_sync(0xffffffffu, a.x, o); a.y += __shfl_xor_sync(0xffffffffu, a.y, o);
            a.z += __shfl_xor_sync(0xffffffffu, a.z, o); a.w += __shfl_xor_sync(0xffffffffu, a.w, o);
        }
        if (lane < 8) *reinterpret_cast<float4*>(red + warp * 32 + lane * 4) = a;
        cbar();
        if (tid < 32) {
            float r = __uint_as_float((uint32_t)xres << 16);
#pragma unroll
            for (int w = 0; w < 8; ++w) r += red[w * 32 + tid];
            const int pc = tid >> 2, e = tid & 3;
            const int n = 16 * (jr >> 1) + (jr & 1) * 4 + (pc >> 1) + 8 * (e >> 1);
            const int b = 2 * (pc & 1) + (e & 1);
            out[b * DM + n] = __float2bfloat16_rn(r);
        }
    }
}

__device__ void fb_layernorm(const __nv_bfloat16* x, float* xn  ) {
    const int warp = threadIdx.x >> 5, lane = threadIdx.x & 31;
    if (warp < NB) {
        float s = 0.f;
        for (int i = lane; i < DM; i += 32) s += __bfloat162float(x[warp * DM + i]);
        for (int o = 16; o; o >>= 1) s += __shfl_xor_sync(0xffffffffu, s, o);
        const float mean = s / DM;
        float v = 0.f;
        for (int i = lane; i < DM; i += 32) { float d = __bfloat162float(x[warp * DM + i]) - mean; v += d * d; }
        for (int o = 16; o; o >>= 1) v += __shfl_xor_sync(0xffffffffu, v, o);
        const float mb = bf16r(mean);
        const float den = bf16r(sqrtf(bf16r(bf16r(v / DM) + 1e-5f)));
        for (int i = lane; i < DM; i += 32)
            xn[warp * DM + i] = bf16r(bf16r(__bfloat162float(x[warp * DM + i]) - mb) / den);
    }
    __syncthreads();
}

__global__ void fb_proj(const __nv_bfloat16* x, const __nv_bfloat16* wq, const __nv_bfloat16* w1,
                        const __nv_bfloat16* b1) {
    __shared__ float xn[NB * DM];
    fb_layernorm(x, xn);
    const int c = blockIdx.x * blockDim.x + threadIdx.x;
    if (c >= QD + FF) return;
    const bool isq = c < QD;
    const __nv_bfloat16* w = isq ? wq + c : w1 + (c - QD);
    const int pitch = isq ? QD : FF;
    float a[NB] = {};
    for (int k = 0; k < DM; ++k) {
        const float wv = __bfloat162float(w[(size_t)k * pitch]);
        for (int b = 0; b < NB; ++b) a[b] = fmaf(xn[b * DM + k], wv, a[b]);
    }
    for (int b = 0; b < NB; ++b) {
        if (isq) g_fb_q[b * QD + c] = __float2bfloat16_rn(a[b]);
        else {
            const float h = bf16r(bf16r(a[b]) + __bfloat162float(b1[c - QD]));
            g_fb_act[b * FF + c - QD] = __float2bfloat16_rn(mish(h));
        }
    }
}

__global__ void fb_attn(const __nv_bfloat16* kc, const __nv_bfloat16* vc) {
    __shared__ float q[DH], p[WIN], rd[128];
    const int b = blockIdx.x / HQ, h = blockIdx.x % HQ, tid = threadIdx.x;
    const size_t base = ((size_t)(b * HKV + h / 2) * SK + (SK - WIN)) * DH;
    q[tid] = __bfloat162float(g_fb_q[b * QD + h * DH + tid]);
    __syncthreads();
    float m = -INFINITY;
    for (int k = tid; k < WIN; k += 128) {
        float s = 0.f;
        for (int d = 0; d < DH; ++d) s = fmaf(q[d], __bfloat162float(kc[base + (size_t)k * DH + d]), s);
        s *= 0.08838834764831845f;
        p[k] = s;
        m = fmaxf(m, s);
    }
    rd[tid] = m;
    __syncthreads();
    for (int i = 0; i < 128; ++i) m = fmaxf(m, rd[i]);
    __syncthreads();
    float l = 0.f;
    for (int k = tid; k < WIN; k += 128) { p[k] = expf(p[k] - m); l += p[k]; }
    rd[tid] = l;
    __syncthreads();
    l = 0.f;
    for (int i = 0; i < 128; ++i) l += rd[i];
    float o = 0.f;
    for (int k = 0; k < WIN; ++k) o = fmaf(p[k], __bfloat162float(vc[base + (size_t)k * DH + tid]), o);
    g_fb_o[b * QD + h * DH + tid] = __float2bfloat16_rn(o / l);
}

__global__ void fb_out(const __nv_bfloat16* x, const __nv_bfloat16* wo, const __nv_bfloat16* w2,
                       __nv_bfloat16* out) {
    __shared__ float rd[8][NB][32];
    const int n = blockIdx.x * 32 + (threadIdx.x & 31), part = threadIdx.x >> 5;
    float a[NB] = {};
    for (int k = part; k < QD; k += 8) {
        const float wv = __bfloat162float(wo[(size_t)k * DM + n]);
        for (int b = 0; b < NB; ++b) a[b] = fmaf(__bfloat162float(g_fb_o[b * QD + k]), wv, a[b]);
    }
    for (int k = part; k < FF; k += 8) {
        const float wv = __bfloat162float(w2[(size_t)k * DM + n]);
        for (int b = 0; b < NB; ++b) a[b] = fmaf(__bfloat162float(g_fb_act[b * FF + k]), wv, a[b]);
    }
    for (int b = 0; b < NB; ++b) rd[part][b][threadIdx.x & 31] = a[b];
    __syncthreads();
    if (threadIdx.x < 128) {
        const int b = threadIdx.x >> 5, c = threadIdx.x & 31;
        float r = __bfloat162float(x[b * DM + blockIdx.x * 32 + c]);
        for (int i = 0; i < 8; ++i) r += rd[i][b][c];
        out[b * DM + blockIdx.x * 32 + c] = __float2bfloat16_rn(r);
    }
}

void launch_fallback(const __nv_bfloat16* x, const __nv_bfloat16* kc, const __nv_bfloat16* vc,
                     const __nv_bfloat16* wq, const __nv_bfloat16* wo, const __nv_bfloat16* w1,
                     const __nv_bfloat16* b1, const __nv_bfloat16* w2, __nv_bfloat16* out) {
    fb_proj<<<(QD + FF) / 128, 128>>>(x, wq, w1, b1);
    fb_attn<<<NB * HQ, 128>>>(kc, vc);
    fb_out<<<DM / 32, 256>>>(x, wo, w2, out);
}

typedef CUresult (*EncodeFn)(CUtensorMap*, CUtensorMapDataType, cuuint32_t, void*, const cuuint64_t*, const cuuint64_t*,
                             const cuuint32_t*, const cuuint32_t*, CUtensorMapInterleave, CUtensorMapSwizzle,
                             CUtensorMapL2promotion, CUtensorMapFloatOOBfill);

#define L2PROMO CU_TENSOR_MAP_L2_PROMOTION_L2_128B

#define L2PROMO2 CU_TENSOR_MAP_L2_PROMOTION_L2_128B
bool make_map(EncodeFn fn, CUtensorMap* m, const void* base, uint64_t cols, uint64_t rows, uint32_t box_cols,
              uint32_t box_rows, CUtensorMapSwizzle sw) {
    cuuint64_t dims[2] = {cols, rows};
    cuuint64_t strides[1] = {cols * 2};
    cuuint32_t box[2] = {box_cols, box_rows};
    cuuint32_t es[2] = {1, 1};
    return fn(m, CU_TENSOR_MAP_DATA_TYPE_BFLOAT16, 2, const_cast<void*>(base), dims, strides, box, es,
              CU_TENSOR_MAP_INTERLEAVE_NONE, sw, box_cols == 32 ? L2PROMO : L2PROMO2, CU_TENSOR_MAP_FLOAT_OOB_FILL_NONE) == CUDA_SUCCESS;
}

struct HostState {
    int ok;
    EncodeFn encode;
    const void* ptr[6];
    bool maps_ok;
    Maps maps;
};
HostState g_host = {-1, nullptr, {nullptr, nullptr, nullptr, nullptr, nullptr, nullptr}, false, {}};

bool fused_ready(const void* wq, const void* kc, const void* vc, const void* w1, const void* w2, const void* wo) {
    HostState& h = g_host;
    if (h.ok < 0) {
        int dev = 0, sms = 0, occ = 0, coop = 0;
        void* fn = nullptr;
        cudaDriverEntryPointQueryResult qr;
        h.ok = 0;
        if (cudaGetDevice(&dev) == cudaSuccess &&
            cudaDeviceGetAttribute(&sms, cudaDevAttrMultiProcessorCount, dev) == cudaSuccess &&
            cudaFuncSetAttribute(fused_kernel, cudaFuncAttributeMaxDynamicSharedMemorySize, SMEM_BYTES) == cudaSuccess &&
            cudaOccupancyMaxActiveBlocksPerMultiprocessor(&occ, fused_kernel, NTHREADS, SMEM_BYTES) == cudaSuccess &&
            sms * occ >= NCTA &&
            cudaDeviceGetAttribute(&coop, cudaDevAttrCooperativeLaunch, dev) == cudaSuccess && coop &&
            cudaGetDriverEntryPoint("cuTensorMapEncodeTiled", &fn, cudaEnableDefault, &qr) == cudaSuccess &&
            qr == cudaDriverEntryPointSuccess && fn) {
            h.encode = (EncodeFn)fn;
            h.ok = 1;
        }
        (void)cudaGetLastError();
    }
    if (h.ok != 1) return false;
    const void* p[6] = {wq, kc, vc, w1, w2, wo};
    bool same = true;
    for (int i = 0; i < 6; ++i) same = same && h.ptr[i] == p[i];
    if (!same) {
        for (int i = 0; i < 6; ++i) h.ptr[i] = p[i];
        const uint64_t kvlines = (uint64_t)NB * HKV * SK * DH / 64;
        h.maps_ok = make_map(h.encode, &h.maps.wq, wq, QD, DM, 32, 144, CU_TENSOR_MAP_SWIZZLE_64B) &&
                    make_map(h.encode, &h.maps.w1, w1, FF, DM, 32, 144, CU_TENSOR_MAP_SWIZZLE_64B) &&
                    make_map(h.encode, &h.maps.k, kc, 64, kvlines, 64, 128, CU_TENSOR_MAP_SWIZZLE_128B) &&
                    make_map(h.encode, &h.maps.v, vc, 64, kvlines, 64, 128, CU_TENSOR_MAP_SWIZZLE_128B) &&
                    make_map(h.encode, &h.maps.w2, w2, 64, (uint64_t)FF * DM / 64, 64, 144, CU_TENSOR_MAP_SWIZZLE_128B) &&
                    make_map(h.encode, &h.maps.wo, wo, 64, (uint64_t)QD * DM / 64, 64, 144, CU_TENSOR_MAP_SWIZZLE_128B);
    }
    return h.maps_ok;
}

}

extern "C" void kernel_launch(void* const* d_in, const int* in_sizes, int n_in, void* d_out, int out_size) {
    const __nv_bfloat16* x = (const __nv_bfloat16*)d_in[0];
    const __nv_bfloat16* kc = (const __nv_bfloat16*)d_in[1];
    const __nv_bfloat16* vc = (const __nv_bfloat16*)d_in[2];
    const __nv_bfloat16* wq = (const __nv_bfloat16*)d_in[3];
    const __nv_bfloat16* wo = (const __nv_bfloat16*)d_in[4];
    const __nv_bfloat16* w1 = (const __nv_bfloat16*)d_in[6];
    const __nv_bfloat16* b1 = (const __nv_bfloat16*)d_in[7];
    const __nv_bfloat16* w2 = (const __nv_bfloat16*)d_in[8];
    __nv_bfloat16* out = (__nv_bfloat16*)d_out;
    if (fused_ready(wq, kc, vc, w1, w2, wo)) {
        cudaLaunchConfig_t cfg = {};
        cfg.gridDim = dim3(NCTA);
        cfg.blockDim = dim3(NTHREADS);
        cfg.dynamicSmemBytes = SMEM_BYTES;
        cfg.stream = 0;
        cudaLaunchAttribute at[1];
        at[0].id = cudaLaunchAttributeCooperative;
        at[0].val.cooperative = 1;
        cfg.attrs = at;
        cfg.numAttrs = 1;
        if (cudaLaunchKernelEx(&cfg, fused_kernel, g_host.maps, x, b1, out) == cudaSuccess) return;
        (void)cudaGetLastError();
    }
    launch_fallback(x, kc, vc, wq, wo, w1, b1, w2, out);
}
```
